```python
import torch

def _softmax(x, axis=-1):
    return torch.softmax(x, dim=axis)
def _gelu(x):
    return torch.nn.functional.gelu(x, approximate="tanh")
def _silu(x):
    return torch.nn.functional.silu(x)
def _sigmoid(x):
    return torch.sigmoid(x)
def _layernorm(x, axis=-1, eps=1e-5):
    m = x.mean(dim=axis, keepdim=True)
    v = x.var(dim=axis, keepdim=True, unbiased=False)
    return (x - m) / torch.sqrt(v + eps)
def _scatter_add(tgt, idx, src, axis=0):
    return tgt.clone().index_add_(axis, idx, src)
def _segment_sum(src, seg, n):
    out = torch.zeros((n,) + src.shape[1:], dtype=src.dtype)
    return out.index_add_(0, seg, src)
def _pad(x, pw):
    flat = tuple(v for pair in reversed(pw) for v in pair)
    return torch.nn.functional.pad(x, flat)

kernel_name = 'sequential_preLN__compressed_kv_cla__glu_gated_reglu__prompt'

def setup_inputs():

    _w = (lambda a: (lambda t: t.to(torch.bfloat16) if t.is_floating_point() else t)(torch.as_tensor(a)))
    def _A_setup():
        B, H, Sq, Sk, D, M = 1, 32, 2048, 2048, 128, 512
        Dc = 4 * D
        return {
            "x": _w((lambda *s: torch.randn(*s, dtype=torch.bfloat16) * 0.05)(B, Sq, M)),
            "c_kv": _w((lambda *s: torch.randn(*s, dtype=torch.bfloat16) * 0.4)(B, Sk, Dc)),
            "w_q": _w((lambda *s: torch.randn(*s, dtype=torch.bfloat16) * 1.6)(M, H, D) * (M ** -0.5)),
            "w_uk": _w((lambda *s: torch.randn(*s, dtype=torch.bfloat16) * 1.6)(Dc, H, D) * (Dc ** -0.5)),
            "w_uv": _w((lambda *s: torch.randn(*s, dtype=torch.bfloat16) * 0.4)(Dc, H, D) * (Dc ** -0.5)),
            "w_o": _w((lambda *s: torch.randn(*s, dtype=torch.bfloat16) * 0.4)(H, D, M) * ((H * D) ** -0.5)),
        }
    _A_in = _A_setup()

    def _B_setup():
        B, S, D, F = 1, 2048, 512, 1376
        return {
            "x": _w((lambda *s: torch.randn(*s, dtype=torch.bfloat16) * 0.05)(B, S, D)),
            "W_gate": _w((lambda *s: torch.randn(*s, dtype=torch.bfloat16) * 0.2)(D, F) * (2.0 / D) ** 0.5),
            "W_up": _w((lambda *s: torch.randn(*s, dtype=torch.bfloat16) * 0.2)(D, F) * (2.0 / D) ** 0.5),
            "W_down": _w((lambda *s: torch.randn(*s, dtype=torch.bfloat16) * 0.2)(F, D) * (1.0 / F) ** 0.5),
        }
    _B_in = _B_setup()

    return {
        "A_x": _A_in["x"],
        "A_c_kv": _A_in["c_kv"],
        "A_w_q": _A_in["w_q"],
        "A_w_uk": _A_in["w_uk"],
        "A_w_uv": _A_in["w_uv"],
        "A_w_o": _A_in["w_o"],
        "B_x": _B_in["x"],
        "B_W_gate": _B_in["W_gate"],
        "B_W_up": _B_in["W_up"],
        "B_W_down": _B_in["W_down"],
    }

def reference(A_x, A_c_kv, A_w_q, A_w_uk, A_w_uv, A_w_o, B_x, B_W_gate, B_W_up, B_W_down):
    def _A_ref(x, c_kv, w_q, w_uk, w_uv, w_o):
        B, Sq, M = x.shape[0], x.shape[1], x.shape[2]
        Sk = c_kv.shape[1]
        H, D = w_q.shape[1], w_q.shape[2]
        q = torch.einsum("bqm,mhd->bhqd", x, w_q)
        k = torch.einsum("bkc,chd->bhkd", c_kv, w_uk)
        v = torch.einsum("bkc,chd->bhkd", c_kv, w_uv)
        scores = torch.einsum("bhqd,bhkd->bhqk", q, k) * (D ** -0.5)
        off = Sk - Sq
        qi = torch.arange(Sq)[:, None]
        kj = torch.arange(Sk)[None, :]
        cmask = kj <= (qi + off)
        scores = torch.where(cmask[None, None], scores, -1e9)
        p = _softmax(scores, axis=-1)
        ctx = torch.einsum("bhqk,bhkd->bhqd", p, v)
        return torch.einsum("bhqd,hdm->bqm", ctx, w_o)

    def _B_ref(x, W_gate, W_up, W_down):
        gate = torch.einsum("bsd,df->bsf", x, W_gate)
        up = torch.einsum("bsd,df->bsf", x, W_up)
        gate = gate * (lambda x, dt: x.to(dt))(gate > 0, gate.dtype)
        h = gate * up
        return torch.einsum("bsf,fd->bsd", h, W_down)

    x = A_x
    h = x + _A_ref(_layernorm(x, axis=-1), A_c_kv, A_w_q, A_w_uk, A_w_uv, A_w_o)
    h2 = h + _B_ref(_layernorm(h, axis=-1), B_W_gate, B_W_up, B_W_down)
    return h2
```

```cpp
#include <cuda_runtime.h>
#include <cuda_bf16.h>
#include <cuda.h>
#include <stdint.h>

namespace {

constexpr int SEQ = 2048, DM = 512, NH = 32, HD = 128, FF = 1376;
constexpr int NRB = 16;
constexpr int TILE_B = 32768;
constexpr int HALF_B = 16384;
constexpr int NFT = 22;

__device__ __align__(1024) uint8_t g_q[NH * NRB * TILE_B];
__device__ __align__(1024) uint8_t g_k[NH * NRB * TILE_B];
__device__ __align__(1024) uint8_t g_v[NH * NRB * TILE_B];
__device__ __align__(1024) uint8_t g_part[NRB * 8 * 8 * 8192];
__device__ __align__(1024) uint8_t g_h[SEQ * DM * 2];
__device__ __align__(1024) uint8_t g_hn[NRB * 8 * HALF_B];
__device__ __align__(1024) uint8_t g_act[NRB * NFT * HALF_B];
__device__ int g_cnt[NRB];

__device__ __forceinline__ uint32_t smem_u32(const void* p) { return (uint32_t)__cvta_generic_to_shared(p); }
__device__ __forceinline__ void mbar_init(uint32_t bar, uint32_t cnt) { asm volatile("mbarrier.init.shared::cta.b64 [%0], %1;" :: "r"(bar), "r"(cnt)); }
__device__ __forceinline__ void mbar_init_fence() { asm volatile("fence.mbarrier_init.release.cluster;" ::: "memory"); }
__device__ __forceinline__ void mbar_expect_tx(uint32_t bar, uint32_t bytes) { asm volatile("mbarrier.arrive.expect_tx.shared::cta.b64 _, [%0], %1;" :: "r"(bar), "r"(bytes) : "memory"); }
__device__ __forceinline__ void mbar_arrive_if(uint32_t bar, bool p) {
  asm volatile("{\n.reg .pred q;\nsetp.ne.u32 q, %1, 0;\n@q mbarrier.arrive.shared::cta.b64 _, [%0];\n}" :: "r"(bar), "r"((uint32_t)p) : "memory");
}
__device__ __forceinline__ void mbar_arrive_remote_if(uint32_t bar, uint32_t cta, bool p) {
  asm volatile("{\n.reg .pred q;\n.reg .b32 ra;\nsetp.ne.u32 q, %2, 0;\nmapa.shared::cluster.u32 ra, %0, %1;\n@q mbarrier.arrive.shared::cluster.b64 _, [ra];\n}"
               :: "r"(bar), "r"(cta), "r"((uint32_t)p) : "memory");
}
__device__ __forceinline__ void mbar_wait(uint32_t bar, uint32_t parity) {
  asm volatile("{\n.reg .pred p;\n.reg .u32 n;\nmov.u32 n, 0;\n"
               "LAB_WAIT:\nmbarrier.try_wait.parity.shared::cta.b64 p, [%0], %1;\n@p bra LAB_DONE;\n"
               "add.u32 n, n, 1;\nsetp.lt.u32 p, n, 4194304;\n@p bra LAB_WAIT;\ntrap;\nLAB_DONE:\n}" :: "r"(bar), "r"(parity) : "memory");
}
__device__ __forceinline__ void mbar_wait_cluster(uint32_t bar, uint32_t parity) {
  asm volatile("{\n.reg .pred p;\n.reg .u32 n;\nmov.u32 n, 0;\n"
               "LAB_WAIT:\nmbarrier.try_wait.parity.acquire.cluster.shared::cta.b64 p, [%0], %1;\n@p bra LAB_DONE;\n"
               "add.u32 n, n, 1;\nsetp.lt.u32 p, n, 4194304;\n@p bra LAB_WAIT;\ntrap;\nLAB_DONE:\n}" :: "r"(bar), "r"(parity) : "memory");
}
__device__ __forceinline__ bool mbar_test(uint32_t bar, uint32_t parity) {
  uint32_t ok;
  asm volatile("{\n.reg .pred p;\nmbarrier.test_wait.parity.shared::cta.b64 p, [%1], %2;\nselp.u32 %0, 1, 0, p;\n}" : "=r"(ok) : "r"(bar), "r"(parity) : "memory");
  return ok;
}
__device__ __forceinline__ void bulk_load(uint32_t dst, const void* src, uint32_t bytes, uint32_t bar) {
  asm volatile("cp.async.bulk.shared::cluster.global.mbarrier::complete_tx::bytes [%0], [%1], %2, [%3];" :: "r"(dst), "l"(src), "r"(bytes), "r"(bar) : "memory");
}
__device__ __forceinline__ void bulk_store(void* dst, uint32_t src, uint32_t bytes) {
  asm volatile("cp.async.bulk.global.shared::cta.bulk_group [%0], [%1], %2;" :: "l"(dst), "r"(src), "r"(bytes) : "memory");
}
__device__ __forceinline__ void tma_load_2d(uint32_t dst, const CUtensorMap* map, uint32_t bar, int c0, int c1) {
  asm volatile("cp.async.bulk.tensor.2d.shared::cluster.global.mbarrier::complete_tx::bytes [%0], [%1, {%3, %4}], [%2];"
               :: "r"(dst), "l"(map), "r"(bar), "r"(c0), "r"(c1) : "memory");
}
__device__ __forceinline__ void tma_load_2d_mc(uint32_t dst, const CUtensorMap* map, uint32_t bar, int c0, int c1, uint16_t mask) {
  asm volatile("cp.async.bulk.tensor.2d.shared::cluster.global.mbarrier::complete_tx::bytes.multicast::cluster [%0], [%1, {%3, %4}], [%2], %5;"
               :: "r"(dst), "l"(map), "r"(bar), "r"(c0), "r"(c1), "h"(mask) : "memory");
}
__device__ __forceinline__ void tma_store_2d(const CUtensorMap* map, uint32_t src, int c0, int c1) {
  asm volatile("cp.async.bulk.tensor.2d.global.shared::cta.bulk_group [%0, {%2, %3}], [%1];" :: "l"(map), "r"(src), "r"(c0), "r"(c1) : "memory");
}
__device__ __forceinline__ void prefetch_map(const CUtensorMap* map) { asm volatile("prefetch.tensormap [%0];" :: "l"(map) : "memory"); }
__device__ __forceinline__ void bulk_commit() { asm volatile("cp.async.bulk.commit_group;" ::: "memory"); }
template <int N> __device__ __forceinline__ void bulk_wait_read() { asm volatile("cp.async.bulk.wait_group.read %0;" :: "n"(N) : "memory"); }
template <int N> __device__ __forceinline__ void bulk_wait() { asm volatile("cp.async.bulk.wait_group %0;" :: "n"(N) : "memory"); }
__device__ __forceinline__ void fence_async_smem() { asm volatile("fence.proxy.async.shared::cta;" ::: "memory"); }
__device__ __forceinline__ void cluster_sync() { asm volatile("barrier.cluster.arrive.release.aligned;\nbarrier.cluster.wait.acquire.aligned;" ::: "memory"); }
__device__ __forceinline__ uint32_t cluster_rank() { uint32_t r; asm volatile("mov.u32 %0, %%cluster_ctarank;" : "=r"(r)); return r; }
__device__ __forceinline__ void pdl_launch() { asm volatile("griddepcontrol.launch_dependents;" ::: "memory"); }
__device__ __forceinline__ void pdl_wait() { asm volatile("griddepcontrol.wait;" ::: "memory"); }
__device__ __forceinline__ void wg_fence() { asm volatile("wgmma.fence.sync.aligned;" ::: "memory"); }
__device__ __forceinline__ void wg_commit() { asm volatile("wgmma.commit_group.sync.aligned;" ::: "memory"); }
template <int N> __device__ __forceinline__ void wg_wait() { asm volatile("wgmma.wait_group.sync.aligned %0;" :: "n"(N) : "memory"); }
template <int N> __device__ __forceinline__ void fence_regs(float (&r)[N]) {
#pragma unroll
  for (int i = 0; i < N; i++) asm volatile("" : "+f"(r[i]) :: "memory");
}
template <int N> __device__ __forceinline__ void fence_regs(uint32_t (&r)[N]) {
#pragma unroll
  for (int i = 0; i < N; i++) asm volatile("" : "+r"(r[i]) :: "memory");
}
constexpr uint32_t DESC_HI = (1024u >> 4) | (1u << 30);
__device__ __forceinline__ uint32_t desc_lo(uint32_t addr, uint32_t lbo) { return ((addr & 0x3FFFF) >> 4) | ((lbo >> 4) << 16); }
__device__ __forceinline__ uint64_t desc_from(uint32_t lo) { uint64_t d; asm("mov.b64 %0, {%1, %2};" : "=l"(d) : "r"(lo), "r"(DESC_HI)); return d; }
__device__ __forceinline__ void ldsm_x4(uint32_t addr, uint32_t& r0, uint32_t& r1, uint32_t& r2, uint32_t& r3) {
  asm volatile("ldmatrix.sync.aligned.m8n8.x4.shared.b16 {%0, %1, %2, %3}, [%4];" : "=r"(r0), "=r"(r1), "=r"(r2), "=r"(r3) : "r"(addr) : "memory");
}
__device__ __forceinline__ void stsm_x4(uint32_t addr, uint32_t r0, uint32_t r1, uint32_t r2, uint32_t r3) {
  asm volatile("stmatrix.sync.aligned.m8n8.x4.shared.b16 [%0], {%1, %2, %3, %4};" :: "r"(addr), "r"(r0), "r"(r1), "r"(r2), "r"(r3) : "memory");
}
__device__ __forceinline__ void mma_16816(float& c0, float& c1, float& c2, float& c3, uint32_t a0, uint32_t a1, uint32_t a2, uint32_t a3, uint32_t b0, uint32_t b1) {
  asm volatile("mma.sync.aligned.m16n8k16.row.col.f32.bf16.bf16.f32 {%0, %1, %2, %3}, {%4, %5, %6, %7}, {%8, %9}, {%0, %1, %2, %3};"
               : "+f"(c0), "+f"(c1), "+f"(c2), "+f"(c3) : "r"(a0), "r"(a1), "r"(a2), "r"(a3), "r"(b0), "r"(b1));
}
__device__ __forceinline__ uint32_t pack_bf16(float lo, float hi) { uint32_t r; asm("cvt.rn.bf16x2.f32 %0, %1, %2;" : "=r"(r) : "f"(hi), "f"(lo)); return r; }
__device__ __forceinline__ float bf_lo(uint32_t v) { return __uint_as_float(v << 16); }
__device__ __forceinline__ float bf_hi(uint32_t v) { return __uint_as_float(v & 0xffff0000u); }
__device__ __forceinline__ float bf_round(float x) { return bf_lo(pack_bf16(x, 0.f)); }
__device__ __forceinline__ uint32_t bf2_sub(uint32_t a, uint32_t b) { uint32_t r; asm("sub.rn.bf16x2 %0, %1, %2;" : "=r"(r) : "r"(a), "r"(b)); return r; }
__device__ __forceinline__ uint32_t bf2_mul(uint32_t a, uint32_t b) { uint32_t r; asm("mul.rn.bf16x2 %0, %1, %2;" : "=r"(r) : "r"(a), "r"(b)); return r; }
__device__ __forceinline__ uint32_t bf2_fma(uint32_t a, uint32_t b, uint32_t c) { uint32_t r; asm("fma.rn.bf16x2 %0, %1, %2, %3;" : "=r"(r) : "r"(a), "r"(b), "r"(c)); return r; }
__device__ __forceinline__ float ex2(float x) { float y; asm("ex2.approx.ftz.f32 %0, %1;" : "=f"(y) : "f"(x)); return y; }
__device__ __forceinline__ float rcp_fast(float x) { float y; asm("rcp.approx.ftz.f32 %0, %1;" : "=f"(y) : "f"(x)); return y; }
__device__ __forceinline__ void bar_sync(int id, int n) { asm volatile("bar.sync %0, %1;" :: "r"(id), "r"(n) : "memory"); }
__device__ __forceinline__ void bar_arrive(int id, int n) { asm volatile("bar.arrive %0, %1;" :: "r"(id), "r"(n) : "memory"); }
template <int R> __device__ __forceinline__ void reg_inc() { asm volatile("setmaxnreg.inc.sync.aligned.u32 %0;" :: "n"(R)); }
template <int R> __device__ __forceinline__ void reg_dec() { asm volatile("setmaxnreg.dec.sync.aligned.u32 %0;" :: "n"(R)); }
__device__ __forceinline__ void anchor_sts(uint32_t addr, float x) { asm volatile("st.volatile.shared.f32 [%0], %1;" :: "r"(addr), "f"(x) : "memory"); }

template <int TB> __device__ __forceinline__ void wgmma_rs_n128(float (&d)[64], uint32_t a0, uint32_t a1, uint32_t a2, uint32_t a3, uint64_t db, int scale_d) {
  asm volatile("{\n.reg .pred p;\nsetp.ne.b32 p, %69, 0;\n"
    "wgmma.mma_async.sync.aligned.m64n128k16.f32.bf16.bf16 "
    "{%0, %1, %2, %3, %4, %5, %6, %7, %8, %9, %10, %11, %12, %13, %14, %15, %16, %17, %18, %19, %20, %21, %22, %23, %24, %25, %26, %27, %28, %29, %30, %31, %32, %33, %34, %35, %36, %37, %38, %39, %40, %41, %42, %43, %44, %45, %46, %47, %48, %49, %50, %51, %52, %53, %54, %55, %56, %57, %58, %59, %60, %61, %62, %63}, "
    "{%64, %65, %66, %67}, %68, p, 1, 1, %70;\n}"
    : "+f"(d[0]), "+f"(d[1]), "+f"(d[2]), "+f"(d[3]), "+f"(d[4]), "+f"(d[5]), "+f"(d[6]), "+f"(d[7]),
      "+f"(d[8]), "+f"(d[9]), "+f"(d[10]), "+f"(d[11]), "+f"(d[12]), "+f"(d[13]), "+f"(d[14]), "+f"(d[15]),
      "+f"(d[16]), "+f"(d[17]), "+f"(d[18]), "+f"(d[19]), "+f"(d[20]), "+f"(d[21]), "+f"(d[22]), "+f"(d[23]),
      "+f"(d[24]), "+f"(d[25]), "+f"(d[26]), "+f"(d[27]), "+f"(d[28]), "+f"(d[29]), "+f"(d[30]), "+f"(d[31]),
      "+f"(d[32]), "+f"(d[33]), "+f"(d[34]), "+f"(d[35]), "+f"(d[36]), "+f"(d[37]), "+f"(d[38]), "+f"(d[39]),
      "+f"(d[40]), "+f"(d[41]), "+f"(d[42]), "+f"(d[43]), "+f"(d[44]), "+f"(d[45]), "+f"(d[46]), "+f"(d[47]),
      "+f"(d[48]), "+f"(d[49]), "+f"(d[50]), "+f"(d[51]), "+f"(d[52]), "+f"(d[53]), "+f"(d[54]), "+f"(d[55]),
      "+f"(d[56]), "+f"(d[57]), "+f"(d[58]), "+f"(d[59]), "+f"(d[60]), "+f"(d[61]), "+f"(d[62]), "+f"(d[63])
    : "r"(a0), "r"(a1), "r"(a2), "r"(a3), "l"(db), "r"(scale_d), "n"(TB));
}
template <int TA, int TB> __device__ __forceinline__ void wgmma_ss_n128(float (&d)[64], uint64_t da, uint64_t db, int scale_d) {
  asm volatile("{\n.reg .pred p;\nsetp.ne.b32 p, %66, 0;\n"
    "wgmma.mma_async.sync.aligned.m64n128k16.f32.bf16.bf16 "
    "{%0, %1, %2, %3, %4, %5, %6, %7, %8, %9, %10, %11, %12, %13, %14, %15, %16, %17, %18, %19, %20, %21, %22, %23, %24, %25, %26, %27, %28, %29, %30, %31, %32, %33, %34, %35, %36, %37, %38, %39, %40, %41, %42, %43, %44, %45, %46, %47, %48, %49, %50, %51, %52, %53, %54, %55, %56, %57, %58, %59, %60, %61, %62, %63}, "
    "%64, %65, p, 1, 1, %67, %68;\n}"
    : "+f"(d[0]), "+f"(d[1]), "+f"(d[2]), "+f"(d[3]), "+f"(d[4]), "+f"(d[5]), "+f"(d[6]), "+f"(d[7]),
      "+f"(d[8]), "+f"(d[9]), "+f"(d[10]), "+f"(d[11]), "+f"(d[12]), "+f"(d[13]), "+f"(d[14]), "+f"(d[15]),
      "+f"(d[16]), "+f"(d[17]), "+f"(d[18]), "+f"(d[19]), "+f"(d[20]), "+f"(d[21]), "+f"(d[22]), "+f"(d[23]),
      "+f"(d[24]), "+f"(d[25]), "+f"(d[26]), "+f"(d[27]), "+f"(d[28]), "+f"(d[29]), "+f"(d[30]), "+f"(d[31]),
      "+f"(d[32]), "+f"(d[33]), "+f"(d[34]), "+f"(d[35]), "+f"(d[36]), "+f"(d[37]), "+f"(d[38]), "+f"(d[39]),
      "+f"(d[40]), "+f"(d[41]), "+f"(d[42]), "+f"(d[43]), "+f"(d[44]), "+f"(d[45]), "+f"(d[46]), "+f"(d[47]),
      "+f"(d[48]), "+f"(d[49]), "+f"(d[50]), "+f"(d[51]), "+f"(d[52]), "+f"(d[53]), "+f"(d[54]), "+f"(d[55]),
      "+f"(d[56]), "+f"(d[57]), "+f"(d[58]), "+f"(d[59]), "+f"(d[60]), "+f"(d[61]), "+f"(d[62]), "+f"(d[63])
    : "l"(da), "l"(db), "r"(scale_d), "n"(TA), "n"(TB));
}
template <int TA, int TB> __device__ __forceinline__ void wgmma_ss_n256(float (&d)[128], uint64_t da, uint64_t db, int scale_d) {
  asm volatile("{\n.reg .pred p;\nsetp.ne.b32 p, %130, 0;\n"
    "wgmma.mma_async.sync.aligned.m64n256k16.f32.bf16.bf16 "
    "{%0, %1, %2, %3, %4, %5, %6, %7, %8, %9, %10, %11, %12, %13, %14, %15, %16, %17, %18, %19, %20, %21, %22, %23, %24, %25, %26, %27, %28, %29, %30, %31, %32, %33, %34, %35, %36, %37, %38, %39, %40, %41, %42, %43, %44, %45, %46, %47, %48, %49, %50, %51, %52, %53, %54, %55, %56, %57, %58, %59, %60, %61, %62, %63, %64, %65, %66, %67, %68, %69, %70, %71, %72, %73, %74, %75, %76, %77, %78, %79, %80, %81, %82, %83, %84, %85, %86, %87, %88, %89, %90, %91, %92, %93, %94, %95, %96, %97, %98, %99, %100, %101, %102, %103, %104, %105, %106, %107, %108, %109, %110, %111, %112, %113, %114, %115, %116, %117, %118, %119, %120, %121, %122, %123, %124, %125, %126, %127}, "
    "%128, %129, p, 1, 1, %131, %132;\n}"
    : "+f"(d[0]), "+f"(d[1]), "+f"(d[2]), "+f"(d[3]), "+f"(d[4]), "+f"(d[5]), "+f"(d[6]), "+f"(d[7]),
      "+f"(d[8]), "+f"(d[9]), "+f"(d[10]), "+f"(d[11]), "+f"(d[12]), "+f"(d[13]), "+f"(d[14]), "+f"(d[15]),
      "+f"(d[16]), "+f"(d[17]), "+f"(d[18]), "+f"(d[19]), "+f"(d[20]), "+f"(d[21]), "+f"(d[22]), "+f"(d[23]),
      "+f"(d[24]), "+f"(d[25]), "+f"(d[26]), "+f"(d[27]), "+f"(d[28]), "+f"(d[29]), "+f"(d[30]), "+f"(d[31]),
      "+f"(d[32]), "+f"(d[33]), "+f"(d[34]), "+f"(d[35]), "+f"(d[36]), "+f"(d[37]), "+f"(d[38]), "+f"(d[39]),
      "+f"(d[40]), "+f"(d[41]), "+f"(d[42]), "+f"(d[43]), "+f"(d[44]), "+f"(d[45]), "+f"(d[46]), "+f"(d[47]),
      "+f"(d[48]), "+f"(d[49]), "+f"(d[50]), "+f"(d[51]), "+f"(d[52]), "+f"(d[53]), "+f"(d[54]), "+f"(d[55]),
      "+f"(d[56]), "+f"(d[57]), "+f"(d[58]), "+f"(d[59]), "+f"(d[60]), "+f"(d[61]), "+f"(d[62]), "+f"(d[63]),
      "+f"(d[64]), "+f"(d[65]), "+f"(d[66]), "+f"(d[67]), "+f"(d[68]), "+f"(d[69]), "+f"(d[70]), "+f"(d[71]),
      "+f"(d[72]), "+f"(d[73]), "+f"(d[74]), "+f"(d[75]), "+f"(d[76]), "+f"(d[77]), "+f"(d[78]), "+f"(d[79]),
      "+f"(d[80]), "+f"(d[81]), "+f"(d[82]), "+f"(d[83]), "+f"(d[84]), "+f"(d[85]), "+f"(d[86]), "+f"(d[87]),
      "+f"(d[88]), "+f"(d[89]), "+f"(d[90]), "+f"(d[91]), "+f"(d[92]), "+f"(d[93]), "+f"(d[94]), "+f"(d[95]),
      "+f"(d[96]), "+f"(d[97]), "+f"(d[98]), "+f"(d[99]), "+f"(d[100]), "+f"(d[101]), "+f"(d[102]), "+f"(d[103]),
      "+f"(d[104]), "+f"(d[105]), "+f"(d[106]), "+f"(d[107]), "+f"(d[108]), "+f"(d[109]), "+f"(d[110]), "+f"(d[111]),
      "+f"(d[112]), "+f"(d[113]), "+f"(d[114]), "+f"(d[115]), "+f"(d[116]), "+f"(d[117]), "+f"(d[118]), "+f"(d[119]),
      "+f"(d[120]), "+f"(d[121]), "+f"(d[122]), "+f"(d[123]), "+f"(d[124]), "+f"(d[125]), "+f"(d[126]), "+f"(d[127])
    : "l"(da), "l"(db), "r"(scale_d), "n"(TA), "n"(TB));
}
template <int TB> __device__ __forceinline__ void wgmma_rs_n64(float (&d)[32], uint32_t a0, uint32_t a1, uint32_t a2, uint32_t a3, uint64_t db, int scale_d) {
  asm volatile("{\n.reg .pred p;\nsetp.ne.b32 p, %37, 0;\n"
    "wgmma.mma_async.sync.aligned.m64n64k16.f32.bf16.bf16 "
    "{%0, %1, %2, %3, %4, %5, %6, %7, %8, %9, %10, %11, %12, %13, %14, %15, %16, %17, %18, %19, %20, %21, %22, %23, %24, %25, %26, %27, %28, %29, %30, %31}, "
    "{%32, %33, %34, %35}, %36, p, 1, 1, %38;\n}"
    : "+f"(d[0]), "+f"(d[1]), "+f"(d[2]), "+f"(d[3]), "+f"(d[4]), "+f"(d[5]), "+f"(d[6]), "+f"(d[7]),
      "+f"(d[8]), "+f"(d[9]), "+f"(d[10]), "+f"(d[11]), "+f"(d[12]), "+f"(d[13]), "+f"(d[14]), "+f"(d[15]),
      "+f"(d[16]), "+f"(d[17]), "+f"(d[18]), "+f"(d[19]), "+f"(d[20]), "+f"(d[21]), "+f"(d[22]), "+f"(d[23]),
      "+f"(d[24]), "+f"(d[25]), "+f"(d[26]), "+f"(d[27]), "+f"(d[28]), "+f"(d[29]), "+f"(d[30]), "+f"(d[31])
    : "r"(a0), "r"(a1), "r"(a2), "r"(a3), "l"(db), "r"(scale_d), "n"(TB));
}


constexpr int NS = 6;
constexpr int RING_STG = NS * TILE_B;
constexpr int RING_BAR = (NS + 1) * TILE_B;
constexpr int RING_SMEM = RING_BAR + 1024 + 256;
struct Ring {
  uint32_t s, ph;
  __device__ __forceinline__ void next() { if (++s == NS) { s = 0; ph ^= 1; } }
};

__device__ __forceinline__ void issue_mn(float (&acc)[64], const uint32_t* A, uint32_t slot, int accumulate) {
  const uint32_t lo = desc_lo(slot, HALF_B);
#pragma unroll
  for (int kk = 0; kk < 8; kk++)
    wgmma_rs_n128<1>(acc, A[4 * kk], A[4 * kk + 1], A[4 * kk + 2], A[4 * kk + 3], desc_from(lo + kk * 128), (kk > 0) ? 1 : accumulate);
}
__device__ __forceinline__ void issue_km(float (&acc)[64], const uint32_t* A, uint32_t slot) {
  const uint32_t lo = desc_lo(slot, 16);
#pragma unroll
  for (int kk = 0; kk < 8; kk++)
    wgmma_rs_n128<0>(acc, A[4 * kk], A[4 * kk + 1], A[4 * kk + 2], A[4 * kk + 3], desc_from(lo + (kk >> 2) * 1024 + (kk & 3) * 2), kk > 0);
}
__device__ __forceinline__ void load_frags(uint32_t* A, uint32_t slot, int row0, int lane) {
  const uint32_t row = row0 + (lane & 7) + ((lane >> 3) & 1) * 8;
  const uint32_t base = slot + row * 128;
#pragma unroll
  for (int kk = 0; kk < 8; kk++) {
    const uint32_t c16 = (kk & 3) * 2 + (lane >> 4);
    ldsm_x4(base + (kk >> 2) * HALF_B + ((c16 ^ (row & 7)) << 4), A[4 * kk], A[4 * kk + 1], A[4 * kk + 2], A[4 * kk + 3]);
  }
}
__device__ __forceinline__ void stage_tile(const float (&O)[64], float s0, float s1, uint32_t stg, int lane) {
  const uint32_t row = (lane & 7) + ((lane >> 3) & 1) * 8;
  const uint32_t a = stg + row * 128;
#pragma unroll
  for (int kk = 0; kk < 8; kk++) {
    const uint32_t c16 = (kk & 3) * 2 + (lane >> 4);
    stsm_x4(a + (kk >> 2) * 2048 + ((c16 ^ (row & 7)) << 4),
            pack_bf16(O[8 * kk] * s0, O[8 * kk + 1] * s0), pack_bf16(O[8 * kk + 2] * s1, O[8 * kk + 3] * s1),
            pack_bf16(O[8 * kk + 4] * s0, O[8 * kk + 5] * s0), pack_bf16(O[8 * kk + 6] * s1, O[8 * kk + 7] * s1));
  }
}
__device__ __forceinline__ void stage_tile(const float (&O)[64], uint32_t stg, int lane) {
  const uint32_t row = (lane & 7) + ((lane >> 3) & 1) * 8;
  const uint32_t a = stg + row * 128;
#pragma unroll
  for (int kk = 0; kk < 8; kk++) {
    const uint32_t c16 = (kk & 3) * 2 + (lane >> 4);
    stsm_x4(a + (kk >> 2) * 2048 + ((c16 ^ (row & 7)) << 4),
            pack_bf16(O[8 * kk], O[8 * kk + 1]), pack_bf16(O[8 * kk + 2], O[8 * kk + 3]),
            pack_bf16(O[8 * kk + 4], O[8 * kk + 5]), pack_bf16(O[8 * kk + 6], O[8 * kk + 7]));
  }
}
__device__ __forceinline__ void store_tile_rows(uint8_t* tile, int row0, uint32_t stg, bool el) {
  fence_async_smem();
  __syncwarp();
  if (el) {
    bulk_store(tile + row0 * 128, stg, 2048);
    bulk_store(tile + HALF_B + row0 * 128, stg + 2048, 2048);
    bulk_commit();
  }
}

__device__ __forceinline__ void layernorm_frags(uint32_t (&A)[128], int lane) {
  constexpr uint32_t ONES = 0x3F803F80u;
  float c0 = 0.f, c1 = 0.f, c2 = 0.f, c3 = 0.f;
#pragma unroll
  for (int k = 0; k < 32; k++) mma_16816(c0, c1, c2, c3, A[4 * k], A[4 * k + 1], A[4 * k + 2], A[4 * k + 3], ONES, ONES);
  const uint32_t m0 = pack_bf16(c0 * (1.f / DM), c0 * (1.f / DM)), m1 = pack_bf16(c2 * (1.f / DM), c2 * (1.f / DM));
#pragma unroll
  for (int i = 0; i < 128; i++) A[i] = bf2_sub(A[i], (i & 1) ? m1 : m0);
  float s0 = 0.f, s1 = 0.f, s2 = 0.f, s3 = 0.f;
  float p0 = 0.f, p1 = 0.f, p2 = 0.f, p3 = 0.f;
  float q0 = 0.f, q1 = 0.f, q2 = 0.f, q3 = 0.f;
#pragma unroll
  for (int k = 0; k < 32; k++) {
    mma_16816(s0, s1, s2, s3, A[4 * k], A[4 * k + 1], A[4 * k + 2], A[4 * k + 3], ONES, ONES);
    mma_16816(p0, p1, p2, p3, A[4 * k], A[4 * k + 1], A[4 * k + 2], A[4 * k + 3], A[4 * k], A[4 * k + 2]);
    mma_16816(q0, q1, q2, q3, A[4 * k], A[4 * k + 1], A[4 * k + 2], A[4 * k + 3], A[4 * k + 1], A[4 * k + 3]);
  }
  const int r = lane >> 2, src = (lane & ~3) + (r >> 1);
  const float d0 = __shfl_sync(0xffffffff, (r & 1) ? p1 : p0, src), d1 = __shfl_sync(0xffffffff, (r & 1) ? q3 : q2, src);
  const float e0 = s0 * (1.f / DM), e1 = s2 * (1.f / DM);
  const float v0 = fmaxf(d0 * (1.f / DM) - e0 * e0, 0.f), v1 = fmaxf(d1 * (1.f / DM) - e1 * e1, 0.f);
  const float i0 = 1.f / bf_round(sqrtf(bf_round(bf_round(v0) + 1e-5f))), i1 = 1.f / bf_round(sqrtf(bf_round(bf_round(v1) + 1e-5f)));
  const float h0 = bf_round(i0), h1 = bf_round(i1);
  const uint32_t hi0 = pack_bf16(h0, h0), lo0 = pack_bf16(i0 - h0, i0 - h0), hi1 = pack_bf16(h1, h1), lo1 = pack_bf16(i1 - h1, i1 - h1);
#pragma unroll
  for (int i = 0; i < 128; i++) A[i] = bf2_fma(A[i], (i & 1) ? hi1 : hi0, bf2_mul(A[i], (i & 1) ? lo1 : lo0));
}

struct ProjMaps { CUtensorMap x, c, wq, wuk, wuv; };

__global__ void __launch_bounds__(384, 1) proj_kernel(const __grid_constant__ ProjMaps maps) {
  extern __shared__ uint8_t smem_raw[];
  const uint32_t sb = (smem_u32(smem_raw) + 1023) & ~1023u;
  const uint32_t full0 = sb + RING_BAR, empty0 = full0 + 8 * NS;
  const int rb = blockIdx.x >> 3, j = blockIdx.x & 7;
  const bool is_x = j < 3;
  const int t0 = is_x ? j * 11 : (j - 3) * 13, t1 = is_x ? min(32, t0 + 11) : min(64, t0 + 13);
  if (threadIdx.x == 0) {
    for (int i = 0; i < NS; i++) { mbar_init(full0 + 8 * i, 1); mbar_init(empty0 + 8 * i, 8); }
    mbar_init_fence();
    if (blockIdx.x == 0) for (int i = 0; i < NRB; i++) g_cnt[i] = 0;
  }
  __syncthreads();
  pdl_launch();
  const int wg = __shfl_sync(0xffffffff, threadIdx.x >> 7, 0);
  if (wg == 2) {
    reg_dec<40>();
    if (threadIdx.x == 256) {
      Ring r{0, 1};
      const CUtensorMap* am = is_x ? &maps.x : &maps.c;
      for (int kc = 0; kc < 4; kc++) {
        mbar_expect_tx(full0 + 8 * r.s, TILE_B);
        tma_load_2d(sb + r.s * TILE_B, am, full0 + 8 * r.s, kc * 128, rb * 128);
        tma_load_2d(sb + r.s * TILE_B + HALF_B, am, full0 + 8 * r.s, kc * 128 + 64, rb * 128);
        r.next();
      }
      for (int t = t0; t < t1; t++) {
        const CUtensorMap* wm = is_x ? &maps.wq : (t < 32 ? &maps.wuk : &maps.wuv);
        const int n0 = (t & 31) * 128;
        for (int kc = 0; kc < 4; kc++) {
          mbar_wait(empty0 + 8 * r.s, r.ph);
          mbar_expect_tx(full0 + 8 * r.s, TILE_B);
          tma_load_2d(sb + r.s * TILE_B, wm, full0 + 8 * r.s, n0, kc * 128);
          tma_load_2d(sb + r.s * TILE_B + HALF_B, wm, full0 + 8 * r.s, n0 + 64, kc * 128);
          r.next();
        }
      }
    }
  } else {
    reg_inc<232>();
    const int tid = threadIdx.x & 127, warp = __shfl_sync(0xffffffff, tid >> 5, 0), lane = tid & 31;
    const bool el = lane == 0;
    const uint32_t stg = sb + RING_STG + wg * 16384 + warp * 4096;
    const int row0 = wg * 64 + warp * 16;
    Ring r{0, 0};
    uint32_t A[128];
    float acc[64];
#pragma unroll
    for (int kc = 0; kc < 4; kc++) {
      mbar_wait(full0 + 8 * r.s, r.ph);
      load_frags(&A[32 * kc], sb + r.s * TILE_B, row0, lane);
      __syncwarp();
      mbar_arrive_if(empty0 + 8 * r.s, el);
      r.next();
    }
    if (is_x) layernorm_frags(A, lane);
    if (wg == 1) bar_arrive(1, 256);
    for (int t = t0; t < t1; t++) {
      bar_sync(1 + wg, 256);
      fence_regs(A); fence_regs(acc);
      uint32_t prev = 0;
#pragma unroll
      for (int kc = 0; kc < 4; kc++) {
        mbar_wait(full0 + 8 * r.s, r.ph);
        if (kc == 0) wg_fence();
        issue_mn(acc, &A[32 * kc], sb + r.s * TILE_B, kc > 0);
        wg_commit();
        if (kc == 3) bar_arrive(1 + (wg ^ 1), 256);
        if (kc > 0) { wg_wait<1>(); mbar_arrive_if(empty0 + 8 * prev, el); }
        prev = r.s;
        r.next();
      }
      wg_wait<0>();
      fence_regs(acc); fence_regs(A);
      mbar_arrive_if(empty0 + 8 * prev, el);
      if (el) bulk_wait_read<0>();
      __syncwarp();
      stage_tile(acc, stg, lane);
      uint8_t* base = is_x ? g_q : (t < 32 ? g_k : g_v);
      store_tile_rows(base + (size_t)((t & 31) * NRB + rb) * TILE_B, row0, stg, el);
    }
    if (el) bulk_wait<0>();
  }
}

constexpr float SM_C = 0.08838834764831845f * 1.4426950408889634f;
constexpr float SM_LIMIT = 1048576.f;
struct AttnSched { uint8_t n[132]; uint16_t item[132][8]; };

__device__ __forceinline__ void apply_mask(float (&S)[64], int thr) {
#pragma unroll
  for (int b = 0; b < 16; b++) {
    if (8 * b > thr) S[4 * b] = -INFINITY;
    if (8 * b + 1 > thr) S[4 * b + 1] = -INFINITY;
    if (8 * b - 8 > thr) S[4 * b + 2] = -INFINITY;
    if (8 * b - 7 > thr) S[4 * b + 3] = -INFINITY;
  }
}
__device__ __forceinline__ float quad_max(float x) {
  x = fmaxf(x, __shfl_xor_sync(0xffffffff, x, 1));
  return fmaxf(x, __shfl_xor_sync(0xffffffff, x, 2));
}
__device__ __forceinline__ float quad_sum(float x) {
  x += __shfl_xor_sync(0xffffffff, x, 1);
  return x + __shfl_xor_sync(0xffffffff, x, 2);
}
template <int B0, int B1>
__device__ __forceinline__ void exp_range(float (&S)[64], float n0, float n1, float (&a)[4]) {
#pragma unroll
  for (int b = B0; b < B1; b++) {
    S[4 * b] = ex2(fmaf(S[4 * b], SM_C, n0)); S[4 * b + 1] = ex2(fmaf(S[4 * b + 1], SM_C, n0));
    S[4 * b + 2] = ex2(fmaf(S[4 * b + 2], SM_C, n1)); S[4 * b + 3] = ex2(fmaf(S[4 * b + 3], SM_C, n1));
    if (b == 0) { a[0] = S[0]; a[1] = S[1]; a[2] = S[2]; a[3] = S[3]; }
    else { a[0] += S[4 * b]; a[1] += S[4 * b + 1]; a[2] += S[4 * b + 2]; a[3] += S[4 * b + 3]; }
  }
}
__device__ __forceinline__ void cvt_p(uint32_t (&P)[32], const float (&S)[64]) {
#pragma unroll
  for (int i = 0; i < 32; i++) P[i] = pack_bf16(S[2 * i], S[2 * i + 1]);
}
__device__ __forceinline__ void true_max_shift(const float (&S)[64], float& n0, float& n1) {
  float x0 = -INFINITY, x1 = -INFINITY;
#pragma unroll
  for (int b = 0; b < 16; b++) { x0 = fmaxf(x0, fmaxf(S[4 * b], S[4 * b + 1])); x1 = fmaxf(x1, fmaxf(S[4 * b + 2], S[4 * b + 3])); }
  n0 = -SM_C * quad_max(x0); n1 = -SM_C * quad_max(x1);
}
__device__ __forceinline__ void slow_block(float (&S)[64], float (&O)[64], uint32_t (&P)[32], const uint32_t (&Q)[32], uint32_t kslot, int lane,
                                           bool diag, int thr, bool first, float& n0, float& n1, float& l0, float& l1, float& r0, float& r1) {
#pragma unroll
  for (int i = 0; i < 64; i++) S[i] = 0.f;
  const uint32_t krow = (lane & 7) + ((lane >> 4) << 3);
  const uint32_t kbase = kslot + krow * 128;
#pragma unroll
  for (int kk = 0; kk < 8; kk++) {
    const uint32_t c16 = (kk & 3) * 2 + ((lane >> 3) & 1);
    const uint32_t a = kbase + (kk >> 2) * HALF_B + ((c16 ^ (krow & 7)) << 4);
#pragma unroll
    for (int bb = 0; bb < 8; bb++) {
      uint32_t b0, b1, b2, b3;
      ldsm_x4(a + bb * 2048, b0, b1, b2, b3);
      mma_16816(S[8 * bb], S[8 * bb + 1], S[8 * bb + 2], S[8 * bb + 3], Q[4 * kk], Q[4 * kk + 1], Q[4 * kk + 2], Q[4 * kk + 3], b0, b1);
      mma_16816(S[8 * bb + 4], S[8 * bb + 5], S[8 * bb + 6], S[8 * bb + 7], Q[4 * kk], Q[4 * kk + 1], Q[4 * kk + 2], Q[4 * kk + 3], b2, b3);
    }
  }
  if (diag) apply_mask(S, thr);
  float m0, m1;
  true_max_shift(S, m0, m1);
  m0 = fminf(n0, m0); m1 = fminf(n1, m1);
  if (!first) {
    const float a0 = ex2(m0 - n0), a1 = ex2(m1 - n1);
    l0 *= a0; l1 *= a1;
#pragma unroll
    for (int b = 0; b < 16; b++) { O[4 * b] *= a0; O[4 * b + 1] *= a0; O[4 * b + 2] *= a1; O[4 * b + 3] *= a1; }
  }
  n0 = m0; n1 = m1;
  float a[4];
  exp_range<0, 16>(S, n0, n1, a);
  r0 = a[0] + a[1]; r1 = a[2] + a[3];
  cvt_p(P, S);
}

__global__ void __launch_bounds__(384, 1) attn_kernel(const __grid_constant__ AttnSched sched) {
  extern __shared__ uint8_t smem_raw[];
  const uint32_t sb = (smem_u32(smem_raw) + 1023) & ~1023u;
  const uint32_t full0 = sb + RING_BAR, empty0 = full0 + 8 * NS;
  const int cid = blockIdx.x;
  const int nitems = sched.n[cid];
  if (threadIdx.x == 0) {
    for (int i = 0; i < NS; i++) { mbar_init(full0 + 8 * i, 1); mbar_init(empty0 + 8 * i, 8); }
    mbar_init_fence();
  }
  __syncthreads();
  pdl_launch();
  const int wg = __shfl_sync(0xffffffff, threadIdx.x >> 7, 0);
  if (wg == 2) {
    reg_dec<40>();
    if (threadIdx.x == 256) {
      Ring r{0, 1};
      auto load_tile = [&](const uint8_t* src) {
        mbar_wait(empty0 + 8 * r.s, r.ph);
        mbar_expect_tx(full0 + 8 * r.s, TILE_B);
        bulk_load(sb + r.s * TILE_B, src, TILE_B, full0 + 8 * r.s);
        r.next();
      };
      pdl_wait();
      const uint8_t* vprev = nullptr;
      if (nitems > 0) load_tile(g_q + (size_t)sched.item[cid][0] * TILE_B);
      for (int it = 0; it < nitems; it++) {
        const int item = sched.item[cid][it];
        const int h = item >> 4, nb = (item & 15) + 1;
        const uint8_t* kb = g_k + (size_t)h * NRB * TILE_B;
        const uint8_t* vb = g_v + (size_t)h * NRB * TILE_B;
        for (int j = 0; j < nb; j++) {
          load_tile(kb + (size_t)j * TILE_B);
          if (vprev) load_tile(vprev);
          vprev = vb + (size_t)j * TILE_B;
        }
        if (it + 1 < nitems) load_tile(g_q + (size_t)sched.item[cid][it + 1] * TILE_B);
      }
      if (vprev) load_tile(vprev);
    }
  } else {
    reg_inc<232>();
    const int tid = threadIdx.x & 127, warp = __shfl_sync(0xffffffff, tid >> 5, 0), lane = tid & 31;
    const bool el = lane == 0;
    const uint32_t stg = sb + RING_STG + wg * 16384 + warp * 4096;
    const int row0 = wg * 64 + warp * 16;
    const int thr = row0 + (lane >> 2) - 2 * (lane & 3);
    const uint32_t anchor_a = sb + RING_BAR + 128 + (lane & 3) * 4;
    Ring r{0, 0};
    float O[64], S[64];
    uint32_t P[32], Q[32];
    float n0 = 0.f, n1 = 0.f, l0 = 0.f, l1 = 0.f;
    auto load_q_at = [&](const Ring& q) {
      mbar_wait(full0 + 8 * q.s, q.ph);
      load_frags(Q, sb + q.s * TILE_B, row0, lane);
      __syncwarp();
      mbar_arrive_if(empty0 + 8 * q.s, el);
    };
    if (nitems > 0) {
      load_q_at(r); r.next();
      if (wg == 1) bar_arrive(1, 256);
      int it = 0, nb = (sched.item[cid][0] & 15) + 1;
      {
        const uint32_t ks = r.s;
        mbar_wait(full0 + 8 * r.s, r.ph);
        r.next();
        bar_sync(1 + wg, 256);
        fence_regs(S); fence_regs(Q);
        wg_fence();
        issue_km(S, Q, sb + ks * TILE_B);
        wg_commit();
        bar_arrive(1 + (wg ^ 1), 256);
        wg_wait<0>();
        fence_regs(S); fence_regs(Q);
        mbar_arrive_if(empty0 + 8 * ks, el);
        if (nb == 1) apply_mask(S, thr);
        true_max_shift(S, n0, n1);
        float a[4];
        exp_range<0, 16>(S, n0, n1, a);
        l0 = a[0] + a[1]; l1 = a[2] + a[3];
        cvt_p(P, S);
      }
      int j = 1;
      bool more = true;
      if (nb == 1) {
        if (nitems == 1) more = false;
        else { load_q_at(r); r.next(); it = 1; j = 0; nb = (sched.item[cid][1] & 15) + 1; }
      }
      uint32_t ks = r.s, kph = r.ph; r.next();
      uint32_t vs = r.s, vph = r.ph; r.next();
      bool ready = false, epi = false;
      int prev_acc = 0, pend = 0;
      float i0 = 0.f, i1 = 0.f;
      while (more) {
        if (!ready) { mbar_wait(full0 + 8 * ks, kph); mbar_wait(full0 + 8 * vs, vph); }
        bar_sync(1 + wg, 256);
        fence_regs(S); fence_regs(Q); fence_regs(O); fence_regs(P);
        wg_fence();
        issue_km(S, Q, sb + ks * TILE_B);
        wg_commit();
        const bool first = j == 0, diag = j == nb - 1;
        const bool special = first || diag;
        const uint32_t kcur = ks, vcur = vs;
        const int acc_now = prev_acc;
        if (epi) {
          if (el) bulk_wait_read<0>();
          __syncwarp();
          stage_tile(O, i0, i1, stg, lane);
          store_tile_rows(g_q + (size_t)pend * TILE_B, row0, stg, el);
          epi = false;
          fence_regs(O);
          wg_fence();
        }
        if (first) { i0 = rcp_fast(quad_sum(l0)); i1 = rcp_fast(quad_sum(l1)); pend = sched.item[cid][it - 1]; epi = true; }
        prev_acc = !first;
        const Ring qr = r;
        if (diag) {
          more = it + 1 < nitems;
          if (more) { r.next(); ++it; j = 0; nb = (sched.item[cid][it] & 15) + 1; }
        } else ++j;
        ks = r.s; kph = r.ph;
        ready = false;
        if (more) {
          r.next(); vs = r.s; vph = r.ph; r.next();
          const bool t0 = mbar_test(full0 + 8 * ks, kph), t1 = mbar_test(full0 + 8 * vs, vph);
          ready = t0 && t1;
        }
        issue_mn(O, P, sb + vcur * TILE_B, acc_now);
        wg_commit();
        bar_arrive(1 + (wg ^ 1), 256);
        wg_wait<1>();
        fence_regs(S); fence_regs(Q);
        if (special) {
          if (diag) apply_mask(S, thr);
          if (first) {
            n0 = -SM_C * quad_max(fmaxf(fmaxf(S[0], S[1]), fmaxf(S[4], S[5])));
            n1 = -SM_C * quad_max(fmaxf(fmaxf(S[2], S[3]), fmaxf(S[6], S[7])));
          }
        }
        float a[4];
        exp_range<0, 10>(S, n0, n1, a);
        anchor_sts(anchor_a, (a[0] + a[2]) + (a[1] + a[3]));
        wg_wait<0>();
        fence_regs(O); fence_regs(P);
        mbar_arrive_if(empty0 + 8 * vcur, el);
        exp_range<10, 16>(S, n0, n1, a);
        cvt_p(P, S);
        float r0 = a[0] + a[1], r1 = a[2] + a[3];
        if (__any_sync(0xffffffff, !(fmaxf(r0, r1) < SM_LIMIT)))
          slow_block(S, O, P, Q, sb + kcur * TILE_B, lane, diag, thr, first, n0, n1, l0, l1, r0, r1);
        mbar_arrive_if(empty0 + 8 * kcur, el);
        l0 = first ? r0 : l0 + r0; l1 = first ? r1 : l1 + r1;
        if (diag && more) load_q_at(qr);
      }
      vs = ks;
      mbar_wait(full0 + 8 * vs, kph);
      bar_sync(1 + wg, 256);
      if (epi) {
        if (el) bulk_wait_read<0>();
        __syncwarp();
        stage_tile(O, i0, i1, stg, lane);
      }
      fence_regs(O); fence_regs(P);
      wg_fence();
      issue_mn(O, P, sb + vs * TILE_B, prev_acc);
      wg_commit();
      bar_arrive(1 + (wg ^ 1), 256);
      if (epi) store_tile_rows(g_q + (size_t)pend * TILE_B, row0, stg, el);
      l0 = rcp_fast(quad_sum(l0)); l1 = rcp_fast(quad_sum(l1));
      if (el) bulk_wait_read<0>();
      __syncwarp();
      wg_wait<0>();
      fence_regs(O);
      stage_tile(O, l0, l1, stg, lane);
      store_tile_rows(g_q + (size_t)sched.item[cid][nitems - 1] * TILE_B, row0, stg, el);
    }
    if (el) bulk_wait<0>();
  }
}

constexpr int O_NS = 4, O_STAGE = 49152, O_BAR = O_NS * O_STAGE, O_SMEM = O_BAR + 1024 + 256;

__global__ void __launch_bounds__(384, 1) oproj_kernel(const __grid_constant__ CUtensorMap wo, const __nv_bfloat16* __restrict__ x) {
  extern __shared__ uint8_t smem_raw[];
  const uint32_t sb = (smem_u32(smem_raw) + 1023) & ~1023u;
  const uint32_t full0 = sb + O_BAR, empty0 = full0 + 8 * O_NS;
  const uint32_t rank = cluster_rank();
  const int c = blockIdx.x >> 1, nh = (c >> 2) & 1, ks = c & 3, rb = (c >> 3) * 2 + rank;
  if (threadIdx.x == 0) {
    for (int i = 0; i < O_NS; i++) { mbar_init(full0 + 8 * i, 1); mbar_init(empty0 + 8 * i, 16); }
    mbar_init_fence();
  }
  __syncthreads();
  cluster_sync();
  pdl_launch();
  const int wg = __shfl_sync(0xffffffff, threadIdx.x >> 7, 0);
  if (wg == 2) {
    reg_dec<40>();
    if (threadIdx.x == 256) {
      auto load_b = [&](int i) {
        const uint32_t st = sb + (i % O_NS) * O_STAGE, bar = full0 + 8 * (i % O_NS);
        mbar_expect_tx(bar, O_STAGE);
        const int k0 = ks * 1024 + i * 64;
        tma_load_2d_mc(st + HALF_B + (2 * rank) * 8192, &wo, bar, nh * 256 + (2 * rank) * 64, k0, (uint16_t)3);
        tma_load_2d_mc(st + HALF_B + (2 * rank + 1) * 8192, &wo, bar, nh * 256 + (2 * rank + 1) * 64, k0, (uint16_t)3);
      };
      auto load_a = [&](int i) {
        const int kh = ks * 16 + i;
        bulk_load(sb + (i % O_NS) * O_STAGE, g_q + (size_t)((kh >> 1) * NRB + rb) * TILE_B + (kh & 1) * HALF_B, HALF_B, full0 + 8 * (i % O_NS));
      };
      for (int i = 0; i < O_NS; i++) load_b(i);
      pdl_wait();
      for (int i = 0; i < O_NS; i++) load_a(i);
      for (int i = O_NS; i < 16; i++) {
        mbar_wait(empty0 + 8 * (i % O_NS), ((i / O_NS) & 1) ^ 1);
        load_b(i);
        load_a(i);
      }
    }
  } else {
    reg_inc<232>();
    const int tid = threadIdx.x & 127, warp = __shfl_sync(0xffffffff, tid >> 5, 0), lane = tid & 31;
    const bool el = lane == 0, el1 = lane == 1;
    float acc[128];
#pragma unroll
    for (int i = 0; i < 128; i++) acc[i] = 0.f;
    fence_regs(acc);
    for (int i = 0; i < 16; i++) {
      const uint32_t st = sb + (i % O_NS) * O_STAGE;
      mbar_wait(full0 + 8 * (i % O_NS), (i / O_NS) & 1);
      const uint32_t alo = desc_lo(st + wg * 8192, 16), blo = desc_lo(st + HALF_B, 8192);
      wg_fence();
#pragma unroll
      for (int kk = 0; kk < 4; kk++) wgmma_ss_n256<0, 1>(acc, desc_from(alo + kk * 2), desc_from(blo + kk * 128), 1);
      wg_commit();
      if (i > 0) {
        wg_wait<1>();
        mbar_arrive_if(empty0 + 8 * ((i - 1) % O_NS), el);
        mbar_arrive_remote_if(empty0 + 8 * ((i - 1) % O_NS), rank ^ 1, el1);
      }
    }
    wg_wait<0>();
    fence_regs(acc);
    bar_sync(3, 256);
    const int g = wg * 4 + warp;
    const uint32_t stg = sb + g * 8192;
    {
      const uint32_t row = (lane & 7) + ((lane >> 3) & 1) * 8;
#pragma unroll
      for (int i = 0; i < 16; i++) {
        const uint32_t c16 = 2 * i + (lane >> 4);
        stsm_x4(stg + row * 512 + ((c16 ^ (row & 7)) << 4), pack_bf16(acc[8 * i], acc[8 * i + 1]), pack_bf16(acc[8 * i + 2], acc[8 * i + 3]),
                pack_bf16(acc[8 * i + 4], acc[8 * i + 5]), pack_bf16(acc[8 * i + 6], acc[8 * i + 7]));
      }
    }
    fence_async_smem();
    __syncwarp();
    const int src = nh * 4 + ks;
    if (el) {
      bulk_store(g_part + (size_t)((rb * 8 + g) * 8 + src) * 8192, stg, 8192);
      bulk_commit();
      bulk_wait<0>();
      asm volatile("fence.proxy.async;" ::: "memory");
      __threadfence();
    }
    bar_sync(3, 256);
    if (threadIdx.x == 0) {
      asm volatile("red.release.gpu.global.add.s32 [%0], 1;" :: "l"(&g_cnt[rb]) : "memory");
      int v, n = 0;
      do { asm volatile("ld.acquire.gpu.global.s32 %0, [%1];" : "=r"(v) : "l"(&g_cnt[rb]) : "memory"); } while (v < 8 && ++n < (1 << 24));
    }
    bar_sync(3, 256);
#pragma unroll
    for (int rr2 = 0; rr2 < 2; rr2++) {
      const int rr = g * 2 + rr2, row128 = src * 16 + rr, row = rb * 128 + row128;
      float v[16];
#pragma unroll
      for (int e = 0; e < 16; e++) v[e] = 0.f;
      const uint8_t* pb = g_part + (size_t)((rb * 8 + src) * 8 + (lane >> 4) * 4) * 8192 + rr * 512;
#pragma unroll
      for (int s4 = 0; s4 < 4; s4++) {
#pragma unroll
        for (int e = 0; e < 2; e++) {
          const uint4 u = __ldcg(reinterpret_cast<const uint4*>(pb + s4 * 8192 + ((((lane & 15) * 2 + e) ^ (rr & 7)) << 4)));
          v[8 * e] += bf_lo(u.x); v[8 * e + 1] += bf_hi(u.x); v[8 * e + 2] += bf_lo(u.y); v[8 * e + 3] += bf_hi(u.y);
          v[8 * e + 4] += bf_lo(u.z); v[8 * e + 5] += bf_hi(u.z); v[8 * e + 6] += bf_lo(u.w); v[8 * e + 7] += bf_hi(u.w);
        }
      }
      const uint4* xp = reinterpret_cast<const uint4*>(x + (size_t)row * DM + lane * 16);
      const uint4 x0 = __ldg(xp), x1 = __ldg(xp + 1);
      const uint32_t xw[8] = {x0.x, x0.y, x0.z, x0.w, x1.x, x1.y, x1.z, x1.w};
      uint32_t hw[8];
      float sum = 0.f;
#pragma unroll
      for (int e = 0; e < 8; e++) {
        const uint32_t at = pack_bf16(v[2 * e], v[2 * e + 1]);
        hw[e] = pack_bf16(bf_lo(xw[e]) + bf_lo(at), bf_hi(xw[e]) + bf_hi(at));
        v[2 * e] = bf_lo(hw[e]); v[2 * e + 1] = bf_hi(hw[e]);
        sum += v[2 * e] + v[2 * e + 1];
      }
#pragma unroll
      for (int o = 16; o; o >>= 1) sum += __shfl_xor_sync(0xffffffff, sum, o);
      const float mean = sum * (1.f / DM);
      float sq = 0.f;
#pragma unroll
      for (int e = 0; e < 16; e++) sq = fmaf(v[e] - mean, v[e] - mean, sq);
#pragma unroll
      for (int o = 16; o; o >>= 1) sq += __shfl_xor_sync(0xffffffff, sq, o);
      const float mb = bf_round(mean);
      const float inv = 1.f / bf_round(sqrtf(bf_round(bf_round(sq * (1.f / DM)) + 1e-5f)));
      uint32_t nw[8];
#pragma unroll
      for (int e = 0; e < 8; e++) {
        const uint32_t d = pack_bf16(v[2 * e] - mb, v[2 * e + 1] - mb);
        nw[e] = pack_bf16(bf_lo(d) * inv, bf_hi(d) * inv);
      }
      uint4* hp = reinterpret_cast<uint4*>(g_h + (size_t)row * DM * 2 + lane * 32);
      hp[0] = make_uint4(hw[0], hw[1], hw[2], hw[3]);
      hp[1] = make_uint4(hw[4], hw[5], hw[6], hw[7]);
      uint8_t* np = g_hn + (size_t)(rb * 8 + (lane >> 2)) * HALF_B + row128 * 128;
      *reinterpret_cast<uint4*>(np + ((((lane & 3) * 2) ^ (row128 & 7)) << 4)) = make_uint4(nw[0], nw[1], nw[2], nw[3]);
      *reinterpret_cast<uint4*>(np + ((((lane & 3) * 2 + 1) ^ (row128 & 7)) << 4)) = make_uint4(nw[4], nw[5], nw[6], nw[7]);
    }
  }
  __syncwarp();
  cluster_sync();
}

struct GuMaps { CUtensorMap wg, wu; };

__global__ void __launch_bounds__(384, 1) gu_kernel(const __grid_constant__ GuMaps maps) {
  extern __shared__ uint8_t smem_raw[];
  const uint32_t sb = (smem_u32(smem_raw) + 1023) & ~1023u;
  const uint32_t full0 = sb + RING_BAR, empty0 = full0 + 8 * NS;
  const int rb = blockIdx.x >> 3, j = blockIdx.x & 7;
  const int t0 = j < 6 ? 3 * j : 18 + 2 * (j - 6), t1 = t0 + (j < 6 ? 3 : 2);
  if (threadIdx.x == 0) {
    for (int i = 0; i < NS; i++) { mbar_init(full0 + 8 * i, 1); mbar_init(empty0 + 8 * i, 8); }
    mbar_init_fence();
  }
  __syncthreads();
  pdl_launch();
  const int wg = __shfl_sync(0xffffffff, threadIdx.x >> 7, 0);
  if (wg == 2) {
    reg_dec<40>();
    if (threadIdx.x == 256) {
      auto load_w = [&](uint32_t s, int t, int kc) {
        mbar_expect_tx(full0 + 8 * s, TILE_B);
        tma_load_2d(sb + s * TILE_B, &maps.wg, full0 + 8 * s, t * 64, kc * 128);
        tma_load_2d(sb + s * TILE_B + HALF_B, &maps.wu, full0 + 8 * s, t * 64, kc * 128);
      };
      load_w(4, t0, 0);
      load_w(5, t0, 1);
      pdl_wait();
      for (int kc = 0; kc < 4; kc++) {
        mbar_expect_tx(full0 + 8 * kc, TILE_B);
        bulk_load(sb + kc * TILE_B, g_hn + (size_t)(rb * 8 + 2 * kc) * HALF_B, TILE_B, full0 + 8 * kc);
      }
      Ring r{0, 0};
      for (int u = 2; u < (t1 - t0) * 4; u++) {
        mbar_wait(empty0 + 8 * r.s, r.ph);
        load_w(r.s, t0 + (u >> 2), u & 3);
        r.next();
      }
    }
  } else {
    reg_inc<232>();
    const int tid = threadIdx.x & 127, warp = __shfl_sync(0xffffffff, tid >> 5, 0), lane = tid & 31;
    const bool el = lane == 0;
    const uint32_t stg = sb + RING_STG + wg * 16384 + warp * 4096;
    const int row0 = wg * 64 + warp * 16;
    Ring r{0, 0};
    uint32_t A[128];
    float acc[64];
#pragma unroll
    for (int kc = 0; kc < 4; kc++) {
      mbar_wait(full0 + 8 * r.s, r.ph);
      load_frags(&A[32 * kc], sb + r.s * TILE_B, row0, lane);
      __syncwarp();
      mbar_arrive_if(empty0 + 8 * r.s, el);
      r.next();
    }
    if (wg == 1) bar_arrive(1, 256);
    for (int t = t0; t < t1; t++) {
      bar_sync(1 + wg, 256);
      fence_regs(A); fence_regs(acc);
      uint32_t prev = 0;
#pragma unroll
      for (int kc = 0; kc < 4; kc++) {
        mbar_wait(full0 + 8 * r.s, r.ph);
        if (kc == 0) wg_fence();
        issue_mn(acc, &A[32 * kc], sb + r.s * TILE_B, kc > 0);
        wg_commit();
        if (kc == 3) bar_arrive(1 + (wg ^ 1), 256);
        if (kc > 0) { wg_wait<1>(); mbar_arrive_if(empty0 + 8 * prev, el); }
        prev = r.s;
        r.next();
      }
      wg_wait<0>();
      fence_regs(acc); fence_regs(A);
      mbar_arrive_if(empty0 + 8 * prev, el);
      if (el) bulk_wait_read<0>();
      __syncwarp();
      uint32_t w[16];
#pragma unroll
      for (int i = 0; i < 16; i++) {
        const uint32_t gp = pack_bf16(acc[2 * i], acc[2 * i + 1]), up = pack_bf16(acc[32 + 2 * i], acc[32 + 2 * i + 1]);
        const float g0 = bf_lo(gp), g1 = bf_hi(gp);
        const uint32_t gr = pack_bf16(g0 * (g0 > 0.f ? 1.f : 0.f), g1 * (g1 > 0.f ? 1.f : 0.f));
        w[i] = bf2_mul(gr, up);
      }
      const uint32_t row = (lane & 7) + ((lane >> 3) & 1) * 8;
#pragma unroll
      for (int kk = 0; kk < 4; kk++) {
        const uint32_t c16 = kk * 2 + (lane >> 4);
        stsm_x4(stg + row * 128 + ((c16 ^ (row & 7)) << 4), w[4 * kk], w[4 * kk + 1], w[4 * kk + 2], w[4 * kk + 3]);
      }
      fence_async_smem();
      __syncwarp();
      if (el) { bulk_store(g_act + (size_t)(rb * NFT + t) * HALF_B + row0 * 128, stg, 2048); bulk_commit(); }
    }
    if (el) bulk_wait<0>();
  }
}

constexpr int D_NS = 5, D_X = D_NS * TILE_B, D_H = D_X + 32768, D_BAR = D_H + 16384, D_SMEM = D_BAR + 1024 + 256;
struct DownMaps { CUtensorMap wd, h, out; };

__global__ void __launch_bounds__(384, 1) down_kernel(const __grid_constant__ DownMaps maps) {
  extern __shared__ uint8_t smem_raw[];
  const uint32_t sb = (smem_u32(smem_raw) + 1023) & ~1023u;
  const uint32_t full0 = sb + D_BAR, empty0 = full0 + 8 * D_NS, hbar = empty0 + 8 * D_NS, xbar = hbar + 8;
  const uint32_t rank = cluster_rank();
  const int c = blockIdx.x >> 1, rb = c >> 2, nq = c & 3;
  const int u0 = rank * 11;
  if (threadIdx.x == 0) {
    for (int i = 0; i < D_NS; i++) { mbar_init(full0 + 8 * i, 1); mbar_init(empty0 + 8 * i, 8); }
    mbar_init(hbar, 1); mbar_init(xbar, 128);
    mbar_init_fence();
  }
  __syncthreads();
  cluster_sync();
  pdl_launch();
  const int wg = __shfl_sync(0xffffffff, threadIdx.x >> 7, 0);
  if (wg == 2) {
    reg_dec<40>();
    if (threadIdx.x == 256) {
      auto load_b = [&](int i) {
        const uint32_t st = sb + (i % D_NS) * TILE_B, bar = full0 + 8 * (i % D_NS);
        mbar_expect_tx(bar, TILE_B);
        tma_load_2d(st + HALF_B, &maps.wd, bar, nq * 128, (u0 + i) * 64);
        tma_load_2d(st + HALF_B + 8192, &maps.wd, bar, nq * 128 + 64, (u0 + i) * 64);
      };
      auto load_a = [&](int i) {
        bulk_load(sb + (i % D_NS) * TILE_B, g_act + (size_t)(rb * NFT + u0 + i) * HALF_B, HALF_B, full0 + 8 * (i % D_NS));
      };
      for (int i = 0; i < D_NS; i++) load_b(i);
      pdl_wait();
      for (int i = 0; i < D_NS; i++) load_a(i);
      mbar_expect_tx(hbar, 16384);
      tma_load_2d(sb + D_H, &maps.h, hbar, nq * 128, rb * 128 + rank * 64);
      tma_load_2d(sb + D_H + 8192, &maps.h, hbar, nq * 128 + 64, rb * 128 + rank * 64);
      for (int i = D_NS; i < 11; i++) {
        mbar_wait(empty0 + 8 * (i % D_NS), ((i / D_NS) & 1) ^ 1);
        load_b(i);
        load_a(i);
      }
    }
  } else {
    reg_inc<232>();
    const int tid = threadIdx.x & 127, warp = __shfl_sync(0xffffffff, tid >> 5, 0), lane = tid & 31;
    const bool el = lane == 0;
    float acc[64];
#pragma unroll
    for (int i = 0; i < 64; i++) acc[i] = 0.f;
    fence_regs(acc);
    for (int i = 0; i < 11; i++) {
      const uint32_t st = sb + (i % D_NS) * TILE_B;
      mbar_wait(full0 + 8 * (i % D_NS), (i / D_NS) & 1);
      const uint32_t alo = desc_lo(st + wg * 8192, 16), blo = desc_lo(st + HALF_B, 8192);
      wg_fence();
#pragma unroll
      for (int kk = 0; kk < 4; kk++) wgmma_ss_n128<0, 1>(acc, desc_from(alo + kk * 2), desc_from(blo + kk * 128), 1);
      wg_commit();
      if (i > 0) { wg_wait<1>(); mbar_arrive_if(empty0 + 8 * ((i - 1) % D_NS), el); }
    }
    wg_wait<0>();
    fence_regs(acc);
    if (wg != (int)rank) {
      uint32_t ra, rbar;
      asm volatile("mapa.shared::cluster.u32 %0, %1, %2;" : "=r"(ra) : "r"(sb + D_X + tid * 16), "r"(rank ^ 1));
      asm volatile("mapa.shared::cluster.u32 %0, %1, %2;" : "=r"(rbar) : "r"(xbar), "r"(rank ^ 1));
#pragma unroll
      for (int i = 0; i < 16; i++)
        asm volatile("st.shared::cluster.v4.f32 [%0], {%1, %2, %3, %4};" :: "r"(ra + i * 2048), "f"(acc[4 * i]), "f"(acc[4 * i + 1]), "f"(acc[4 * i + 2]), "f"(acc[4 * i + 3]) : "memory");
      asm volatile("mbarrier.arrive.release.cluster.shared::cluster.b64 _, [%0];" :: "r"(rbar) : "memory");
    } else {
      mbar_wait(hbar, 0);
      mbar_wait_cluster(xbar, 0);
      const uint32_t row = warp * 16 + (lane & 7) + ((lane >> 3) & 1) * 8;
      const uint32_t hb = sb + D_H + row * 128;
#pragma unroll
      for (int kk = 0; kk < 8; kk++) {
        float4 p0, p1;
        asm volatile("ld.shared.v4.f32 {%0, %1, %2, %3}, [%4];" : "=f"(p0.x), "=f"(p0.y), "=f"(p0.z), "=f"(p0.w) : "r"(sb + D_X + tid * 16 + (2 * kk) * 2048) : "memory");
        asm volatile("ld.shared.v4.f32 {%0, %1, %2, %3}, [%4];" : "=f"(p1.x), "=f"(p1.y), "=f"(p1.z), "=f"(p1.w) : "r"(sb + D_X + tid * 16 + (2 * kk + 1) * 2048) : "memory");
        const uint32_t a = hb + (kk >> 2) * 8192 + ((((kk & 3) * 2 + (lane >> 4)) ^ (row & 7)) << 4);
        uint32_t h0, h1, h2, h3;
        ldsm_x4(a, h0, h1, h2, h3);
        const uint32_t d0 = pack_bf16(acc[8 * kk] + p0.x, acc[8 * kk + 1] + p0.y), d1 = pack_bf16(acc[8 * kk + 2] + p0.z, acc[8 * kk + 3] + p0.w);
        const uint32_t d2 = pack_bf16(acc[8 * kk + 4] + p1.x, acc[8 * kk + 5] + p1.y), d3 = pack_bf16(acc[8 * kk + 6] + p1.z, acc[8 * kk + 7] + p1.w);
        stsm_x4(a, pack_bf16(bf_lo(h0) + bf_lo(d0), bf_hi(h0) + bf_hi(d0)), pack_bf16(bf_lo(h1) + bf_lo(d1), bf_hi(h1) + bf_hi(d1)),
                pack_bf16(bf_lo(h2) + bf_lo(d2), bf_hi(h2) + bf_hi(d2)), pack_bf16(bf_lo(h3) + bf_lo(d3), bf_hi(h3) + bf_hi(d3)));
      }
      fence_async_smem();
      __syncwarp();
      if (el) {
        const int orow = rb * 128 + rank * 64 + warp * 16;
        tma_store_2d(&maps.out, sb + D_H + warp * 2048, nq * 128, orow);
        tma_store_2d(&maps.out, sb + D_H + 8192 + warp * 2048, nq * 128 + 64, orow);
        bulk_commit();
        bulk_wait<0>();
      }
    }
  }
  __syncwarp();
  cluster_sync();
}

typedef CUresult (*EncodeTiledFn)(CUtensorMap*, CUtensorMapDataType, cuuint32_t, void*, const cuuint64_t*, const cuuint64_t*, const cuuint32_t*,
                                  const cuuint32_t*, CUtensorMapInterleave, CUtensorMapSwizzle, CUtensorMapL2promotion, CUtensorMapFloatOOBfill);

CUtensorMap make_map(EncodeTiledFn fn, const void* ptr, uint64_t cols, uint64_t rows, uint32_t box_cols, uint32_t box_rows) {
  CUtensorMap m;
  cuuint64_t dims[2] = {cols, rows};
  cuuint64_t strides[1] = {cols * 2};
  cuuint32_t box[2] = {box_cols, box_rows};
  cuuint32_t es[2] = {1, 1};
  fn(&m, CU_TENSOR_MAP_DATA_TYPE_BFLOAT16, 2, const_cast<void*>(ptr), dims, strides, box, es, CU_TENSOR_MAP_INTERLEAVE_NONE,
     CU_TENSOR_MAP_SWIZZLE_128B, CU_TENSOR_MAP_L2_PROMOTION_L2_128B, CU_TENSOR_MAP_FLOAT_OOB_FILL_NONE);
  return m;
}

void make_attn_sched(AttnSched& s, int nworkers) {
  float load[132];
  for (int i = 0; i < 132; i++) { load[i] = 0.f; s.n[i] = 0; }
  for (int qb = NRB - 1; qb >= 0; qb--)
    for (int h = 0; h < NH; h++) {
      int best = -1;
      for (int w = 0; w < nworkers; w++)
        if (s.n[w] < 8 && (best < 0 || load[w] < load[best])) best = w;
      load[best] += qb + 1 + 0.6f;
      s.item[best][s.n[best]++] = (uint16_t)(h * 16 + qb);
    }
}

template <typename... KArgs, typename... Args>
void launch(void (*kern)(KArgs...), int grid, int smem, int cluster, bool pdl, cudaStream_t st, Args... args) {
  cudaLaunchConfig_t cfg = {};
  cfg.gridDim = dim3(grid); cfg.blockDim = dim3(384); cfg.dynamicSmemBytes = smem; cfg.stream = st;
  cudaLaunchAttribute at[2];
  int n = 0;
  if (cluster > 1) { at[n].id = cudaLaunchAttributeClusterDimension; at[n].val.clusterDim.x = cluster; at[n].val.clusterDim.y = 1; at[n].val.clusterDim.z = 1; n++; }
  if (pdl) { at[n].id = cudaLaunchAttributeProgrammaticStreamSerialization; at[n].val.programmaticStreamSerializationAllowed = 1; n++; }
  cfg.attrs = at; cfg.numAttrs = n;
  cudaLaunchKernelEx(&cfg, kern, KArgs(args)...);
}

}

extern "C" void kernel_launch(void* const* d_in, const int* in_sizes, int n_in, void* d_out, int out_size) {
  (void)in_sizes; (void)n_in; (void)out_size;
  static EncodeTiledFn encode = nullptr;
  static AttnSched sched;
  static void* h_ptr = nullptr;
  static int n_sm = 0;
  if (!encode) {
    void* p = nullptr;
    cudaDriverEntryPointQueryResult q;
    cudaGetDriverEntryPoint("cuTensorMapEncodeTiled", &p, cudaEnableDefault, &q);
    encode = (EncodeTiledFn)p;
    cudaDeviceGetAttribute(&n_sm, cudaDevAttrMultiProcessorCount, 0);
    if (n_sm > 132) n_sm = 132;
    make_attn_sched(sched, n_sm);
    cudaGetSymbolAddress(&h_ptr, g_h);
    cudaFuncSetAttribute(proj_kernel, cudaFuncAttributeMaxDynamicSharedMemorySize, RING_SMEM);
    cudaFuncSetAttribute(attn_kernel, cudaFuncAttributeMaxDynamicSharedMemorySize, RING_SMEM);
    cudaFuncSetAttribute(oproj_kernel, cudaFuncAttributeMaxDynamicSharedMemorySize, O_SMEM);
    cudaFuncSetAttribute(gu_kernel, cudaFuncAttributeMaxDynamicSharedMemorySize, RING_SMEM);
    cudaFuncSetAttribute(down_kernel, cudaFuncAttributeMaxDynamicSharedMemorySize, D_SMEM);
  }
  const void *x = d_in[0], *ckv = d_in[1], *wq = d_in[2], *wuk = d_in[3], *wuv = d_in[4], *wo = d_in[5];
  const void *wg = d_in[7], *wu = d_in[8], *wd = d_in[9];
  ProjMaps pm;
  pm.x = make_map(encode, x, DM, SEQ, 64, 128);
  pm.c = make_map(encode, ckv, DM, SEQ, 64, 128);
  pm.wq = make_map(encode, wq, NH * HD, DM, 64, 128);
  pm.wuk = make_map(encode, wuk, NH * HD, DM, 64, 128);
  pm.wuv = make_map(encode, wuv, NH * HD, DM, 64, 128);
  const CUtensorMap wo_map = make_map(encode, wo, DM, NH * HD, 64, 64);
  GuMaps gm;
  gm.wg = make_map(encode, wg, FF, DM, 64, 128);
  gm.wu = make_map(encode, wu, FF, DM, 64, 128);
  DownMaps dm;
  dm.wd = make_map(encode, wd, DM, FF, 64, 64);
  dm.h = make_map(encode, h_ptr, DM, SEQ, 64, 64);
  dm.out = make_map(encode, d_out, DM, SEQ, 64, 16);

  cudaStream_t st = cudaStreamPerThread;
  launch(proj_kernel, 128, RING_SMEM, 1, false, st, pm);
  launch(attn_kernel, n_sm, RING_SMEM, 1, true, st, sched);
  launch(oproj_kernel, 128, O_SMEM, 2, true, st, wo_map, (const __nv_bfloat16*)x);
  launch(gu_kernel, 128, RING_SMEM, 1, true, st, gm);
  launch(down_kernel, 128, D_SMEM, 2, true, st, dm);
}
```

```cpp
#include <cuda_runtime.h>
#include <cuda_bf16.h>
#include <cuda.h>
#include <stdint.h>

namespace {

constexpr int SEQ = 2048, DM = 512, NH = 32, HD = 128, FF = 1376;
constexpr int NRB = 16;
constexpr int TILE_B = 32768;
constexpr int HALF_B = 16384;
constexpr int NFT = 22;

__device__ __align__(1024) uint8_t g_q[NH * NRB * TILE_B];
__device__ __align__(1024) uint8_t g_k[NH * NRB * TILE_B];
__device__ __align__(1024) uint8_t g_v[NH * NRB * TILE_B];
__device__ __align__(1024) uint8_t g_part[NRB * 2 * 4 * 4 * 16384];
__device__ __align__(1024) uint8_t g_h[NRB * 8 * HALF_B];
__device__ __align__(1024) uint8_t g_act[NRB * NFT * HALF_B];
__device__ int g_cnt[4 * NRB];
__device__ __align__(1024) float2 g_stat[NRB * 8 * 128];
__device__ int g_epoch;
__device__ int g_head[NH];
constexpr int HEAD_DONE = 3 * NRB;
__device__ int g_next;

__device__ __forceinline__ uint32_t smem_u32(const void* p) { return (uint32_t)__cvta_generic_to_shared(p); }
__device__ __forceinline__ void mbar_init(uint32_t bar, uint32_t cnt) { asm volatile("mbarrier.init.shared::cta.b64 [%0], %1;" :: "r"(bar), "r"(cnt)); }
__device__ __forceinline__ void mbar_init_fence() { asm volatile("fence.mbarrier_init.release.cluster;" ::: "memory"); }
__device__ __forceinline__ void mbar_expect_tx(uint32_t bar, uint32_t bytes) { asm volatile("mbarrier.arrive.expect_tx.shared::cta.b64 _, [%0], %1;" :: "r"(bar), "r"(bytes) : "memory"); }
__device__ __forceinline__ void mbar_arrive_if(uint32_t bar, bool p) {
  asm volatile("{\n.reg .pred q;\nsetp.ne.u32 q, %1, 0;\n@q mbarrier.arrive.shared::cta.b64 _, [%0];\n}" :: "r"(bar), "r"((uint32_t)p) : "memory");
}
__device__ __forceinline__ void mbar_arrive_remote_if(uint32_t bar, uint32_t cta, bool p) {
  asm volatile("{\n.reg .pred q;\n.reg .b32 ra;\nsetp.ne.u32 q, %2, 0;\nmapa.shared::cluster.u32 ra, %0, %1;\n@q mbarrier.arrive.shared::cluster.b64 _, [ra];\n}"
               :: "r"(bar), "r"(cta), "r"((uint32_t)p) : "memory");
}
__device__ __forceinline__ void mbar_wait(uint32_t bar, uint32_t parity) {
  asm volatile("{\n.reg .pred p;\n.reg .u32 n;\nmov.u32 n, 0;\n"
               "LAB_WAIT:\nmbarrier.try_wait.parity.shared::cta.b64 p, [%0], %1;\n@p bra LAB_DONE;\n"
               "add.u32 n, n, 1;\nsetp.lt.u32 p, n, 4194304;\n@p bra LAB_WAIT;\ntrap;\nLAB_DONE:\n}" :: "r"(bar), "r"(parity) : "memory");
}
__device__ __forceinline__ void mbar_wait_cluster(uint32_t bar, uint32_t parity) {
  asm volatile("{\n.reg .pred p;\n.reg .u32 n;\nmov.u32 n, 0;\n"
               "LAB_WAIT:\nmbarrier.try_wait.parity.acquire.cluster.shared::cta.b64 p, [%0], %1;\n@p bra LAB_DONE;\n"
               "add.u32 n, n, 1;\nsetp.lt.u32 p, n, 4194304;\n@p bra LAB_WAIT;\ntrap;\nLAB_DONE:\n}" :: "r"(bar), "r"(parity) : "memory");
}
__device__ __forceinline__ bool mbar_test(uint32_t bar, uint32_t parity) {
  uint32_t ok;
  asm volatile("{\n.reg .pred p;\nmbarrier.test_wait.parity.shared::cta.b64 p, [%1], %2;\nselp.u32 %0, 1, 0, p;\n}" : "=r"(ok) : "r"(bar), "r"(parity) : "memory");
  return ok;
}
__device__ __forceinline__ void bulk_load(uint32_t dst, const void* src, uint32_t bytes, uint32_t bar) {
  asm volatile("cp.async.bulk.shared::cluster.global.mbarrier::complete_tx::bytes [%0], [%1], %2, [%3];" :: "r"(dst), "l"(src), "r"(bytes), "r"(bar) : "memory");
}
__device__ __forceinline__ void bulk_load_mc(uint32_t dst, const void* src, uint32_t bytes, uint32_t bar, uint16_t mask) {
  asm volatile("cp.async.bulk.shared::cluster.global.mbarrier::complete_tx::bytes.multicast::cluster [%0], [%1], %2, [%3], %4;"
               :: "r"(dst), "l"(src), "r"(bytes), "r"(bar), "h"(mask) : "memory");
}
__device__ __forceinline__ void bulk_prefetch(const void* src, uint32_t bytes) {
  asm volatile("cp.async.bulk.prefetch.L2.global [%0], %1;" :: "l"(src), "r"(bytes) : "memory");
}
__device__ __forceinline__ void bulk_store(void* dst, uint32_t src, uint32_t bytes) {
  asm volatile("cp.async.bulk.global.shared::cta.bulk_group [%0], [%1], %2;" :: "l"(dst), "r"(src), "r"(bytes) : "memory");
}
__device__ __forceinline__ void tma_load_2d(uint32_t dst, const CUtensorMap* map, uint32_t bar, int c0, int c1) {
  asm volatile("cp.async.bulk.tensor.2d.shared::cluster.global.mbarrier::complete_tx::bytes [%0], [%1, {%3, %4}], [%2];"
               :: "r"(dst), "l"(map), "r"(bar), "r"(c0), "r"(c1) : "memory");
}
__device__ __forceinline__ void tma_load_2d_mc(uint32_t dst, const CUtensorMap* map, uint32_t bar, int c0, int c1, uint16_t mask) {
  asm volatile("cp.async.bulk.tensor.2d.shared::cluster.global.mbarrier::complete_tx::bytes.multicast::cluster [%0], [%1, {%3, %4}], [%2], %5;"
               :: "r"(dst), "l"(map), "r"(bar), "r"(c0), "r"(c1), "h"(mask) : "memory");
}
__device__ __forceinline__ void tma_store_2d(const CUtensorMap* map, uint32_t src, int c0, int c1) {
  asm volatile("cp.async.bulk.tensor.2d.global.shared::cta.bulk_group [%0, {%2, %3}], [%1];" :: "l"(map), "r"(src), "r"(c0), "r"(c1) : "memory");
}
__device__ __forceinline__ void prefetch_map(const CUtensorMap* map) { asm volatile("prefetch.tensormap [%0];" :: "l"(map) : "memory"); }
__device__ __forceinline__ void bulk_commit() { asm volatile("cp.async.bulk.commit_group;" ::: "memory"); }
template <int N> __device__ __forceinline__ void bulk_wait_read() { asm volatile("cp.async.bulk.wait_group.read %0;" :: "n"(N) : "memory"); }
template <int N> __device__ __forceinline__ void bulk_wait() { asm volatile("cp.async.bulk.wait_group %0;" :: "n"(N) : "memory"); }
__device__ __forceinline__ void fence_async_smem() { asm volatile("fence.proxy.async.shared::cta;" ::: "memory"); }
__device__ __forceinline__ uint32_t cluster_rank() { uint32_t r; asm volatile("mov.u32 %0, %%cluster_ctarank;" : "=r"(r)); return r; }
__device__ __forceinline__ int fresh_lane() { uint32_t t; asm volatile("mov.u32 %0, %%tid.x;" : "=r"(t)); return t & 31; }
__device__ __forceinline__ void pdl_launch() { asm volatile("griddepcontrol.launch_dependents;" ::: "memory"); }
__device__ __forceinline__ void pdl_wait() { asm volatile("griddepcontrol.wait;" ::: "memory"); }
__device__ __forceinline__ void wg_fence() { asm volatile("wgmma.fence.sync.aligned;" ::: "memory"); }
__device__ __forceinline__ void wg_commit() { asm volatile("wgmma.commit_group.sync.aligned;" ::: "memory"); }
template <int N> __device__ __forceinline__ void wg_wait() { asm volatile("wgmma.wait_group.sync.aligned %0;" :: "n"(N) : "memory"); }
template <int N> __device__ __forceinline__ void fence_regs(float (&r)[N]) {
#pragma unroll
  for (int i = 0; i < N; i++) asm volatile("" : "+f"(r[i]) :: "memory");
}
template <int N> __device__ __forceinline__ void fence_regs(uint32_t (&r)[N]) {
#pragma unroll
  for (int i = 0; i < N; i++) asm volatile("" : "+r"(r[i]) :: "memory");
}
constexpr uint32_t DESC_HI = (1024u >> 4) | (1u << 30);
__device__ __forceinline__ uint32_t desc_lo(uint32_t addr, uint32_t lbo) { return ((addr & 0x3FFFF) >> 4) | ((lbo >> 4) << 16); }
__device__ __forceinline__ uint64_t desc_from(uint32_t lo) { uint64_t d; asm("mov.b64 %0, {%1, %2};" : "=l"(d) : "r"(lo), "r"(DESC_HI)); return d; }
__device__ __forceinline__ void ldsm_x4(uint32_t addr, uint32_t& r0, uint32_t& r1, uint32_t& r2, uint32_t& r3) {
  asm volatile("ldmatrix.sync.aligned.m8n8.x4.shared.b16 {%0, %1, %2, %3}, [%4];" : "=r"(r0), "=r"(r1), "=r"(r2), "=r"(r3) : "r"(addr) : "memory");
}
__device__ __forceinline__ void stsm_x4(uint32_t addr, uint32_t r0, uint32_t r1, uint32_t r2, uint32_t r3) {
  asm volatile("stmatrix.sync.aligned.m8n8.x4.shared.b16 [%0], {%1, %2, %3, %4};" :: "r"(addr), "r"(r0), "r"(r1), "r"(r2), "r"(r3) : "memory");
}
__device__ __forceinline__ void mma_16816(float& c0, float& c1, float& c2, float& c3, uint32_t a0, uint32_t a1, uint32_t a2, uint32_t a3, uint32_t b0, uint32_t b1) {
  asm volatile("mma.sync.aligned.m16n8k16.row.col.f32.bf16.bf16.f32 {%0, %1, %2, %3}, {%4, %5, %6, %7}, {%8, %9}, {%0, %1, %2, %3};"
               : "+f"(c0), "+f"(c1), "+f"(c2), "+f"(c3) : "r"(a0), "r"(a1), "r"(a2), "r"(a3), "r"(b0), "r"(b1));
}
__device__ __forceinline__ uint32_t pack_bf16(float lo, float hi) { uint32_t r; asm("cvt.rn.bf16x2.f32 %0, %1, %2;" : "=r"(r) : "f"(hi), "f"(lo)); return r; }
__device__ __forceinline__ float bf_lo(uint32_t v) { return __uint_as_float(v << 16); }
__device__ __forceinline__ float bf_hi(uint32_t v) { return __uint_as_float(v & 0xffff0000u); }
__device__ __forceinline__ float bf_round(float x) { return bf_lo(pack_bf16(x, 0.f)); }
__device__ __forceinline__ uint32_t bf2_sub(uint32_t a, uint32_t b) { uint32_t r; asm("sub.rn.bf16x2 %0, %1, %2;" : "=r"(r) : "r"(a), "r"(b)); return r; }
__device__ __forceinline__ uint32_t bf2_mul(uint32_t a, uint32_t b) { uint32_t r; asm("mul.rn.bf16x2 %0, %1, %2;" : "=r"(r) : "r"(a), "r"(b)); return r; }
__device__ __forceinline__ uint32_t bf2_relu(uint32_t a) { uint32_t r; asm("max.NaN.bf16x2 %0, %1, %2;" : "=r"(r) : "r"(a), "r"(0u)); return r; }
__device__ __forceinline__ float ex2(float x) { float y; asm("ex2.approx.ftz.f32 %0, %1;" : "=f"(y) : "f"(x)); return y; }
__device__ __forceinline__ float rcp_fast(float x) { float y; asm("rcp.approx.ftz.f32 %0, %1;" : "=f"(y) : "f"(x)); return y; }
__device__ __forceinline__ void bar_sync(int id, int n) { asm volatile("bar.sync %0, %1;" :: "r"(id), "r"(n) : "memory"); }
__device__ __forceinline__ void bar_arrive(int id, int n) { asm volatile("bar.arrive %0, %1;" :: "r"(id), "r"(n) : "memory"); }
template <int R> __device__ __forceinline__ void reg_inc() { asm volatile("setmaxnreg.inc.sync.aligned.u32 %0;" :: "n"(R)); }
template <int R> __device__ __forceinline__ void reg_dec() { asm volatile("setmaxnreg.dec.sync.aligned.u32 %0;" :: "n"(R)); }
__device__ __forceinline__ void anchor_sts(uint32_t addr, float x) { asm volatile("st.volatile.shared.f32 [%0], %1;" :: "r"(addr), "f"(x) : "memory"); }

template <int TB> __device__ __forceinline__ void wgmma_rs_n128(float (&d)[64], uint32_t a0, uint32_t a1, uint32_t a2, uint32_t a3, uint64_t db, int scale_d) {
  asm volatile("{\n.reg .pred p;\nsetp.ne.b32 p, %69, 0;\n"
    "wgmma.mma_async.sync.aligned.m64n128k16.f32.bf16.bf16 "
    "{%0, %1, %2, %3, %4, %5, %6, %7, %8, %9, %10, %11, %12, %13, %14, %15, %16, %17, %18, %19, %20, %21, %22, %23, %24, %25, %26, %27, %28, %29, %30, %31, %32, %33, %34, %35, %36, %37, %38, %39, %40, %41, %42, %43, %44, %45, %46, %47, %48, %49, %50, %51, %52, %53, %54, %55, %56, %57, %58, %59, %60, %61, %62, %63}, "
    "{%64, %65, %66, %67}, %68, p, 1, 1, %70;\n}"
    : "+f"(d[0]), "+f"(d[1]), "+f"(d[2]), "+f"(d[3]), "+f"(d[4]), "+f"(d[5]), "+f"(d[6]), "+f"(d[7]),
      "+f"(d[8]), "+f"(d[9]), "+f"(d[10]), "+f"(d[11]), "+f"(d[12]), "+f"(d[13]), "+f"(d[14]), "+f"(d[15]),
      "+f"(d[16]), "+f"(d[17]), "+f"(d[18]), "+f"(d[19]), "+f"(d[20]), "+f"(d[21]), "+f"(d[22]), "+f"(d[23]),
      "+f"(d[24]), "+f"(d[25]), "+f"(d[26]), "+f"(d[27]), "+f"(d[28]), "+f"(d[29]), "+f"(d[30]), "+f"(d[31]),
      "+f"(d[32]), "+f"(d[33]), "+f"(d[34]), "+f"(d[35]), "+f"(d[36]), "+f"(d[37]), "+f"(d[38]), "+f"(d[39]),
      "+f"(d[40]), "+f"(d[41]), "+f"(d[42]), "+f"(d[43]), "+f"(d[44]), "+f"(d[45]), "+f"(d[46]), "+f"(d[47]),
      "+f"(d[48]), "+f"(d[49]), "+f"(d[50]), "+f"(d[51]), "+f"(d[52]), "+f"(d[53]), "+f"(d[54]), "+f"(d[55]),
      "+f"(d[56]), "+f"(d[57]), "+f"(d[58]), "+f"(d[59]), "+f"(d[60]), "+f"(d[61]), "+f"(d[62]), "+f"(d[63])
    : "r"(a0), "r"(a1), "r"(a2), "r"(a3), "l"(db), "r"(scale_d), "n"(TB));
}
template <int TA, int TB> __device__ __forceinline__ void wgmma_ss_n128(float (&d)[64], uint64_t da, uint64_t db, int scale_d) {
  asm volatile("{\n.reg .pred p;\nsetp.ne.b32 p, %66, 0;\n"
    "wgmma.mma_async.sync.aligned.m64n128k16.f32.bf16.bf16 "
    "{%0, %1, %2, %3, %4, %5, %6, %7, %8, %9, %10, %11, %12, %13, %14, %15, %16, %17, %18, %19, %20, %21, %22, %23, %24, %25, %26, %27, %28, %29, %30, %31, %32, %33, %34, %35, %36, %37, %38, %39, %40, %41, %42, %43, %44, %45, %46, %47, %48, %49, %50, %51, %52, %53, %54, %55, %56, %57, %58, %59, %60, %61, %62, %63}, "
    "%64, %65, p, 1, 1, %67, %68;\n}"
    : "+f"(d[0]), "+f"(d[1]), "+f"(d[2]), "+f"(d[3]), "+f"(d[4]), "+f"(d[5]), "+f"(d[6]), "+f"(d[7]),
      "+f"(d[8]), "+f"(d[9]), "+f"(d[10]), "+f"(d[11]), "+f"(d[12]), "+f"(d[13]), "+f"(d[14]), "+f"(d[15]),
      "+f"(d[16]), "+f"(d[17]), "+f"(d[18]), "+f"(d[19]), "+f"(d[20]), "+f"(d[21]), "+f"(d[22]), "+f"(d[23]),
      "+f"(d[24]), "+f"(d[25]), "+f"(d[26]), "+f"(d[27]), "+f"(d[28]), "+f"(d[29]), "+f"(d[30]), "+f"(d[31]),
      "+f"(d[32]), "+f"(d[33]), "+f"(d[34]), "+f"(d[35]), "+f"(d[36]), "+f"(d[37]), "+f"(d[38]), "+f"(d[39]),
      "+f"(d[40]), "+f"(d[41]), "+f"(d[42]), "+f"(d[43]), "+f"(d[44]), "+f"(d[45]), "+f"(d[46]), "+f"(d[47]),
      "+f"(d[48]), "+f"(d[49]), "+f"(d[50]), "+f"(d[51]), "+f"(d[52]), "+f"(d[53]), "+f"(d[54]), "+f"(d[55]),
      "+f"(d[56]), "+f"(d[57]), "+f"(d[58]), "+f"(d[59]), "+f"(d[60]), "+f"(d[61]), "+f"(d[62]), "+f"(d[63])
    : "l"(da), "l"(db), "r"(scale_d), "n"(TA), "n"(TB));
}
template <int TA, int TB> __device__ __forceinline__ void wgmma_ss_n256(float (&d)[128], uint64_t da, uint64_t db, int scale_d) {
  asm volatile("{\n.reg .pred p;\nsetp.ne.b32 p, %130, 0;\n"
    "wgmma.mma_async.sync.aligned.m64n256k16.f32.bf16.bf16 "
    "{%0, %1, %2, %3, %4, %5, %6, %7, %8, %9, %10, %11, %12, %13, %14, %15, %16, %17, %18, %19, %20, %21, %22, %23, %24, %25, %26, %27, %28, %29, %30, %31, %32, %33, %34, %35, %36, %37, %38, %39, %40, %41, %42, %43, %44, %45, %46, %47, %48, %49, %50, %51, %52, %53, %54, %55, %56, %57, %58, %59, %60, %61, %62, %63, %64, %65, %66, %67, %68, %69, %70, %71, %72, %73, %74, %75, %76, %77, %78, %79, %80, %81, %82, %83, %84, %85, %86, %87, %88, %89, %90, %91, %92, %93, %94, %95, %96, %97, %98, %99, %100, %101, %102, %103, %104, %105, %106, %107, %108, %109, %110, %111, %112, %113, %114, %115, %116, %117, %118, %119, %120, %121, %122, %123, %124, %125, %126, %127}, "
    "%128, %129, p, 1, 1, %131, %132;\n}"
    : "+f"(d[0]), "+f"(d[1]), "+f"(d[2]), "+f"(d[3]), "+f"(d[4]), "+f"(d[5]), "+f"(d[6]), "+f"(d[7]),
      "+f"(d[8]), "+f"(d[9]), "+f"(d[10]), "+f"(d[11]), "+f"(d[12]), "+f"(d[13]), "+f"(d[14]), "+f"(d[15]),
      "+f"(d[16]), "+f"(d[17]), "+f"(d[18]), "+f"(d[19]), "+f"(d[20]), "+f"(d[21]), "+f"(d[22]), "+f"(d[23]),
      "+f"(d[24]), "+f"(d[25]), "+f"(d[26]), "+f"(d[27]), "+f"(d[28]), "+f"(d[29]), "+f"(d[30]), "+f"(d[31]),
      "+f"(d[32]), "+f"(d[33]), "+f"(d[34]), "+f"(d[35]), "+f"(d[36]), "+f"(d[37]), "+f"(d[38]), "+f"(d[39]),
      "+f"(d[40]), "+f"(d[41]), "+f"(d[42]), "+f"(d[43]), "+f"(d[44]), "+f"(d[45]), "+f"(d[46]), "+f"(d[47]),
      "+f"(d[48]), "+f"(d[49]), "+f"(d[50]), "+f"(d[51]), "+f"(d[52]), "+f"(d[53]), "+f"(d[54]), "+f"(d[55]),
      "+f"(d[56]), "+f"(d[57]), "+f"(d[58]), "+f"(d[59]), "+f"(d[60]), "+f"(d[61]), "+f"(d[62]), "+f"(d[63]),
      "+f"(d[64]), "+f"(d[65]), "+f"(d[66]), "+f"(d[67]), "+f"(d[68]), "+f"(d[69]), "+f"(d[70]), "+f"(d[71]),
      "+f"(d[72]), "+f"(d[73]), "+f"(d[74]), "+f"(d[75]), "+f"(d[76]), "+f"(d[77]), "+f"(d[78]), "+f"(d[79]),
      "+f"(d[80]), "+f"(d[81]), "+f"(d[82]), "+f"(d[83]), "+f"(d[84]), "+f"(d[85]), "+f"(d[86]), "+f"(d[87]),
      "+f"(d[88]), "+f"(d[89]), "+f"(d[90]), "+f"(d[91]), "+f"(d[92]), "+f"(d[93]), "+f"(d[94]), "+f"(d[95]),
      "+f"(d[96]), "+f"(d[97]), "+f"(d[98]), "+f"(d[99]), "+f"(d[100]), "+f"(d[101]), "+f"(d[102]), "+f"(d[103]),
      "+f"(d[104]), "+f"(d[105]), "+f"(d[106]), "+f"(d[107]), "+f"(d[108]), "+f"(d[109]), "+f"(d[110]), "+f"(d[111]),
      "+f"(d[112]), "+f"(d[113]), "+f"(d[114]), "+f"(d[115]), "+f"(d[116]), "+f"(d[117]), "+f"(d[118]), "+f"(d[119]),
      "+f"(d[120]), "+f"(d[121]), "+f"(d[122]), "+f"(d[123]), "+f"(d[124]), "+f"(d[125]), "+f"(d[126]), "+f"(d[127])
    : "l"(da), "l"(db), "r"(scale_d), "n"(TA), "n"(TB));
}
template <int TB> __device__ __forceinline__ void wgmma_rs_n64(float (&d)[64], uint32_t a0, uint32_t a1, uint32_t a2, uint32_t a3, uint64_t db, int scale_d) {
  asm volatile("{\n.reg .pred p;\nsetp.ne.b32 p, %37, 0;\n"
    "wgmma.mma_async.sync.aligned.m64n64k16.f32.bf16.bf16 "
    "{%0, %1, %2, %3, %4, %5, %6, %7, %8, %9, %10, %11, %12, %13, %14, %15, %16, %17, %18, %19, %20, %21, %22, %23, %24, %25, %26, %27, %28, %29, %30, %31}, "
    "{%32, %33, %34, %35}, %36, p, 1, 1, %38;\n}"
    : "+f"(d[0]), "+f"(d[1]), "+f"(d[2]), "+f"(d[3]), "+f"(d[4]), "+f"(d[5]), "+f"(d[6]), "+f"(d[7]),
      "+f"(d[8]), "+f"(d[9]), "+f"(d[10]), "+f"(d[11]), "+f"(d[12]), "+f"(d[13]), "+f"(d[14]), "+f"(d[15]),
      "+f"(d[16]), "+f"(d[17]), "+f"(d[18]), "+f"(d[19]), "+f"(d[20]), "+f"(d[21]), "+f"(d[22]), "+f"(d[23]),
      "+f"(d[24]), "+f"(d[25]), "+f"(d[26]), "+f"(d[27]), "+f"(d[28]), "+f"(d[29]), "+f"(d[30]), "+f"(d[31])
    : "r"(a0), "r"(a1), "r"(a2), "r"(a3), "l"(db), "r"(scale_d), "n"(TB));
}


constexpr int NS = 6;
constexpr int RING_STG = NS * TILE_B;
constexpr int RING_BAR = (NS + 1) * TILE_B;
constexpr int RING_PUB = RING_BAR + 160;
constexpr int RING_ITEMS = RING_BAR + 208;
constexpr int RING_SCALE = RING_BAR + 256;
constexpr int RING_SMEM = RING_BAR + 1024 + 256 + 512;
struct Ring {
  uint32_t s, ph;
  __device__ __forceinline__ void next() { if (++s == NS) { s = 0; ph ^= 1; } }
};

__device__ __forceinline__ void issue_mn(float (&acc)[64], const uint32_t* A, uint32_t slot, int accumulate) {
  const uint32_t lo = desc_lo(slot, HALF_B);
#pragma unroll
  for (int kk = 0; kk < 8; kk++)
    wgmma_rs_n128<1>(acc, A[4 * kk], A[4 * kk + 1], A[4 * kk + 2], A[4 * kk + 3], desc_from(lo + kk * 128), (kk > 0) ? 1 : accumulate);
}
__device__ __forceinline__ void issue_km(float (&acc)[64], const uint32_t* A, uint32_t slot) {
  const uint32_t lo = desc_lo(slot, 16);
#pragma unroll
  for (int kk = 0; kk < 8; kk++)
    wgmma_rs_n128<0>(acc, A[4 * kk], A[4 * kk + 1], A[4 * kk + 2], A[4 * kk + 3], desc_from(lo + (kk >> 2) * 1024 + (kk & 3) * 2), kk > 0);
}
__device__ __forceinline__ void load_frags(uint32_t* A, uint32_t slot, int row0, int lane) {
  const uint32_t row = row0 + (lane & 7) + ((lane >> 3) & 1) * 8;
  const uint32_t base = slot + row * 128;
#pragma unroll
  for (int kk = 0; kk < 8; kk++) {
    const uint32_t c16 = (kk & 3) * 2 + (lane >> 4);
    ldsm_x4(base + (kk >> 2) * HALF_B + ((c16 ^ (row & 7)) << 4), A[4 * kk], A[4 * kk + 1], A[4 * kk + 2], A[4 * kk + 3]);
  }
}
__device__ __forceinline__ void stage_tile(const float (&O)[64], float s0, float s1, uint32_t stg, int lane) {
  const uint32_t row = (lane & 7) + ((lane >> 3) & 1) * 8;
  const uint32_t a = stg + row * 128;
#pragma unroll
  for (int kk = 0; kk < 8; kk++) {
    const uint32_t c16 = (kk & 3) * 2 + (lane >> 4);
    stsm_x4(a + (kk >> 2) * 2048 + ((c16 ^ (row & 7)) << 4),
            pack_bf16(O[8 * kk] * s0, O[8 * kk + 1] * s0), pack_bf16(O[8 * kk + 2] * s1, O[8 * kk + 3] * s1),
            pack_bf16(O[8 * kk + 4] * s0, O[8 * kk + 5] * s0), pack_bf16(O[8 * kk + 6] * s1, O[8 * kk + 7] * s1));
  }
}
__device__ __forceinline__ void store_tile_rows(uint8_t* tile, int row0, uint32_t stg, bool el) {
  fence_async_smem();
  __syncwarp();
  if (el) {
    bulk_store(tile + row0 * 128, stg, 2048);
    bulk_store(tile + HALF_B + row0 * 128, stg + 2048, 2048);
    bulk_commit();
  }
}

__device__ __forceinline__ void layernorm_frags(uint32_t (&A)[128], int lane, float& i0, float& i1) {
  constexpr uint32_t ONES = 0x3F803F80u;
  float c[4][4] = {};
#pragma unroll
  for (int k = 0; k < 32; k++) mma_16816(c[k & 3][0], c[k & 3][1], c[k & 3][2], c[k & 3][3], A[4 * k], A[4 * k + 1], A[4 * k + 2], A[4 * k + 3], ONES, ONES);
  const float mean0 = ((c[0][0] + c[1][0]) + (c[2][0] + c[3][0])) * (1.f / DM), mean1 = ((c[0][2] + c[1][2]) + (c[2][2] + c[3][2])) * (1.f / DM);
  const uint32_t m0 = pack_bf16(mean0, mean0), m1 = pack_bf16(mean1, mean1);
#pragma unroll
  for (int i = 0; i < 128; i++) A[i] = bf2_sub(A[i], (i & 1) ? m1 : m0);
  float pp[2][4] = {}, qq[2][4] = {};
#pragma unroll
  for (int k = 0; k < 32; k++) {
    mma_16816(pp[k & 1][0], pp[k & 1][1], pp[k & 1][2], pp[k & 1][3], A[4 * k], A[4 * k + 1], A[4 * k + 2], A[4 * k + 3], A[4 * k], A[4 * k + 2]);
    mma_16816(qq[k & 1][0], qq[k & 1][1], qq[k & 1][2], qq[k & 1][3], A[4 * k], A[4 * k + 1], A[4 * k + 2], A[4 * k + 3], A[4 * k + 1], A[4 * k + 3]);
  }
  const float p[2] = {pp[0][0] + pp[1][0], pp[0][1] + pp[1][1]}, q[4] = {0.f, 0.f, qq[0][2] + qq[1][2], qq[0][3] + qq[1][3]};
  const int r = lane >> 2, src = (lane & ~3) + (r >> 1);
  const float d0 = __shfl_sync(0xffffffff, (r & 1) ? p[1] : p[0], src), d1 = __shfl_sync(0xffffffff, (r & 1) ? q[3] : q[2], src);
  const float e0 = mean0 - bf_lo(m0), e1 = mean1 - bf_lo(m1);
  const float v0 = fmaxf(d0 * (1.f / DM) - e0 * e0, 0.f), v1 = fmaxf(d1 * (1.f / DM) - e1 * e1, 0.f);
  i0 = rcp_fast(bf_round(sqrtf(bf_round(bf_round(v0) + 1e-5f))));
  i1 = rcp_fast(bf_round(sqrtf(bf_round(bf_round(v1) + 1e-5f))));
}

struct ProjMaps { CUtensorMap x, c, wq, wuk, wuv; };
struct FrontSched {
  const uint8_t *wo, *wg, *wu, *wd;
  uint8_t prb[132];
  uint8_t pinfo[132];
};
__device__ __forceinline__ void signal_add(int* ctr) {
  asm volatile("fence.proxy.async.global;" ::: "memory");
  asm volatile("red.release.gpu.global.add.s32 [%0], 1;" :: "l"(ctr) : "memory");
}
__device__ __forceinline__ void signal_after_bulk(int* ctr) {
  asm volatile("fence.proxy.async.global;" ::: "memory");
  asm volatile("red.relaxed.gpu.global.add.s32 [%0], 1;" :: "l"(ctr) : "memory");
}
__device__ __forceinline__ void wait_count(const int* ctr, int target) {
  asm volatile("{\n.reg .pred p;\n.reg .u32 n;\n.reg .s32 v;\nmov.u32 n, 0;\n"
               "LAB_SPIN:\nld.acquire.gpu.global.s32 v, [%0];\nsetp.ge.s32 p, v, %1;\n@p bra LAB_OK;\n"
               "add.u32 n, n, 1;\nsetp.lt.u32 p, n, 8388608;\n@p bra LAB_SPIN;\ntrap;\nLAB_OK:\n"
               "fence.proxy.async.global;\n}" :: "l"(ctr), "r"(target) : "memory");
}

__device__ __forceinline__ void proj_producer(const ProjMaps& maps, int rb, int pinfo, uint32_t sb, Ring& r) {
  const uint32_t full0 = sb + RING_BAR, empty0 = full0 + 8 * NS;
  const bool is_x = pinfo >> 7;
  const int t0 = pinfo & 7, tstep = (pinfo >> 3) & 15, t1 = is_x ? 32 : 64;
  const CUtensorMap* am = is_x ? &maps.x : &maps.c;
  for (int kc = 0; kc < 4; kc++) {
    mbar_expect_tx(full0 + 8 * r.s, TILE_B);
    tma_load_2d(sb + r.s * TILE_B, am, full0 + 8 * r.s, kc * 128, rb * 128);
    tma_load_2d(sb + r.s * TILE_B + HALF_B, am, full0 + 8 * r.s, kc * 128 + 64, rb * 128);
    r.next();
  }
  for (int t = t0; t < t1; t += tstep) {
    const CUtensorMap* wm = is_x ? &maps.wq : ((t & 1) ? &maps.wuv : &maps.wuk);
    const int n0 = (is_x ? t : t >> 1) * 128;
    for (int kc = 0; kc < 4; kc++) {
      mbar_wait(empty0 + 8 * r.s, r.ph);
      mbar_expect_tx(full0 + 8 * r.s, TILE_B);
      tma_load_2d(sb + r.s * TILE_B, wm, full0 + 8 * r.s, n0, kc * 128);
      tma_load_2d(sb + r.s * TILE_B + HALF_B, wm, full0 + 8 * r.s, n0 + 64, kc * 128);
      r.next();
    }
  }
}

__device__ __forceinline__ void proj_publisher(int pinfo, uint32_t sb) {
  const bool is_x = pinfo >> 7;
  const int t0 = pinfo & 7, tstep = (pinfo >> 3) & 15, t1 = is_x ? 32 : 64;
  int n = 0;
  for (int t = t0; t < t1; t += tstep, n++) {
    mbar_wait(sb + RING_PUB + 8 * (n & 1), (n >> 1) & 1);
    signal_add(&g_head[is_x ? t : t >> 1]);
  }
}

__device__ __forceinline__ void proj_consumer(int wg, int rb, int pinfo, uint32_t sb, Ring& r) {
  const uint32_t full0 = sb + RING_BAR, empty0 = full0 + 8 * NS;
  const bool is_x = pinfo >> 7;
  const int t0 = pinfo & 7, tstep = (pinfo >> 3) & 15, t1 = is_x ? 32 : 64;
  const int tid = threadIdx.x & 127, warp = __shfl_sync(0xffffffff, tid >> 5, 0), lane = tid & 31;
  const bool el = lane == 0;
  const uint32_t stg = sb + RING_STG + wg * 16384 + warp * 4096;
  const int row0 = wg * 64 + warp * 16;
  const uint32_t pub0 = sb + RING_PUB;
  int npub = 0;
  uint32_t A[128];
  float acc[64];
#pragma unroll
  for (int kc = 0; kc < 4; kc++) {
    mbar_wait(full0 + 8 * r.s, r.ph);
    load_frags(&A[32 * kc], sb + r.s * TILE_B, row0, lane);
    __syncwarp();
    mbar_arrive_if(empty0 + 8 * r.s, el);
    r.next();
  }
  const uint32_t scale_a = sb + RING_SCALE + (row0 + (lane >> 2)) * 4;
  {
    float i0 = 1.f, i1 = 1.f;
    if (is_x) layernorm_frags(A, lane, i0, i1);
    if ((lane & 3) == 0) {
      asm volatile("st.shared.f32 [%0], %1;" :: "r"(scale_a), "f"(i0) : "memory");
      asm volatile("st.shared.f32 [%0], %1;" :: "r"(scale_a + 32), "f"(i1) : "memory");
    }
    __syncwarp();
  }
  for (int t = t0; t < t1; t += tstep) {
    bar_sync(1 + wg, 256);
    fence_regs(A); fence_regs(acc);
    uint32_t prev = 0;
#pragma unroll
    for (int kc = 0; kc < 4; kc++) {
      mbar_wait(full0 + 8 * r.s, r.ph);
      if (kc == 0) wg_fence();
      issue_mn(acc, &A[32 * kc], sb + r.s * TILE_B, kc > 0);
      wg_commit();
      if (kc == 3) bar_arrive(1 + (wg ^ 1), 256);
      if (kc > 0) { wg_wait<1>(); mbar_arrive_if(empty0 + 8 * prev, el); }
      prev = r.s;
      r.next();
    }
    wg_wait<0>();
    fence_regs(acc); fence_regs(A);
    mbar_arrive_if(empty0 + 8 * prev, el);
    if (el) bulk_wait_read<0>();
    __syncwarp();
    {
      float i0, i1;
      asm volatile("ld.shared.f32 %0, [%1];" : "=f"(i0) : "r"(scale_a) : "memory");
      asm volatile("ld.shared.f32 %0, [%1];" : "=f"(i1) : "r"(scale_a + 32) : "memory");
      stage_tile(acc, i0, i1, stg, lane);
    }
    uint8_t* base = is_x ? g_q : ((t & 1) ? g_v : g_k);
    store_tile_rows(base + (size_t)((is_x ? t : t >> 1) * NRB + rb) * TILE_B, row0, stg, el);
    if (t != t0 && el) { bulk_wait<1>(); mbar_arrive_if(pub0 + 8 * ((npub++) & 1), true); }
  }
  if (el) { bulk_wait<0>(); mbar_arrive_if(pub0 + 8 * (npub & 1), true); }
  __syncwarp();
}

constexpr float SM_C = 0.08838834764831845f * 1.4426950408889634f;
constexpr float SM_LIMIT = 1048576.f;

__device__ __forceinline__ void apply_mask(float (&S)[64], int thr) {
#pragma unroll
  for (int b = 0; b < 16; b++) {
    if (8 * b > thr) S[4 * b] = -INFINITY;
    if (8 * b + 1 > thr) S[4 * b + 1] = -INFINITY;
    if (8 * b - 8 > thr) S[4 * b + 2] = -INFINITY;
    if (8 * b - 7 > thr) S[4 * b + 3] = -INFINITY;
  }
}
__device__ __forceinline__ float quad_max(float x) {
  x = fmaxf(x, __shfl_xor_sync(0xffffffff, x, 1));
  return fmaxf(x, __shfl_xor_sync(0xffffffff, x, 2));
}
__device__ __forceinline__ float quad_sum(float x) {
  x += __shfl_xor_sync(0xffffffff, x, 1);
  return x + __shfl_xor_sync(0xffffffff, x, 2);
}
template <int B0, int B1>
__device__ __forceinline__ void exp_range(float (&S)[64], float n0, float n1, float (&a)[2]) {
#pragma unroll
  for (int b = B0; b < B1; b++) {
    S[4 * b] = ex2(fmaf(S[4 * b], SM_C, n0)); S[4 * b + 1] = ex2(fmaf(S[4 * b + 1], SM_C, n0));
    S[4 * b + 2] = ex2(fmaf(S[4 * b + 2], SM_C, n1)); S[4 * b + 3] = ex2(fmaf(S[4 * b + 3], SM_C, n1));
    if (b == 0) { a[0] = S[0] + S[1]; a[1] = S[2] + S[3]; }
    else { a[0] += S[4 * b]; a[1] += S[4 * b + 2]; a[0] += S[4 * b + 1]; a[1] += S[4 * b + 3]; }
  }
}
__device__ __forceinline__ void cvt_p(uint32_t (&P)[32], const float (&S)[64]) {
#pragma unroll
  for (int i = 0; i < 32; i++) P[i] = pack_bf16(S[2 * i], S[2 * i + 1]);
}
__device__ __forceinline__ void true_max_shift(const float (&S)[64], float& n0, float& n1) {
  float x0 = -INFINITY, x1 = -INFINITY;
#pragma unroll
  for (int b = 0; b < 16; b++) { x0 = fmaxf(x0, fmaxf(S[4 * b], S[4 * b + 1])); x1 = fmaxf(x1, fmaxf(S[4 * b + 2], S[4 * b + 3])); }
  n0 = -SM_C * quad_max(x0); n1 = -SM_C * quad_max(x1);
}
__device__ __forceinline__ void slow_block(float (&S)[64], float (&O)[64], uint32_t (&P)[32], const uint32_t (&Q)[32], uint32_t kslot, int lane,
                                           bool diag, int thr, bool first, float& n0, float& n1, float& l0, float& l1, float& r0, float& r1) {
#pragma unroll
  for (int i = 0; i < 64; i++) S[i] = 0.f;
  const uint32_t krow = (lane & 7) + ((lane >> 4) << 3);
  const uint32_t kbase = kslot + krow * 128;
#pragma unroll
  for (int kk = 0; kk < 8; kk++) {
    const uint32_t c16 = (kk & 3) * 2 + ((lane >> 3) & 1);
    const uint32_t a = kbase + (kk >> 2) * HALF_B + ((c16 ^ (krow & 7)) << 4);
#pragma unroll
    for (int bb = 0; bb < 8; bb++) {
      uint32_t b0, b1, b2, b3;
      ldsm_x4(a + bb * 2048, b0, b1, b2, b3);
      mma_16816(S[8 * bb], S[8 * bb + 1], S[8 * bb + 2], S[8 * bb + 3], Q[4 * kk], Q[4 * kk + 1], Q[4 * kk + 2], Q[4 * kk + 3], b0, b1);
      mma_16816(S[8 * bb + 4], S[8 * bb + 5], S[8 * bb + 6], S[8 * bb + 7], Q[4 * kk], Q[4 * kk + 1], Q[4 * kk + 2], Q[4 * kk + 3], b2, b3);
    }
  }
  if (diag) apply_mask(S, thr);
  float m0, m1;
  true_max_shift(S, m0, m1);
  m0 = fminf(n0, m0); m1 = fminf(n1, m1);
  if (!first) {
    const float a0 = ex2(m0 - n0), a1 = ex2(m1 - n1);
    l0 *= a0; l1 *= a1;
#pragma unroll
    for (int b = 0; b < 16; b++) { O[4 * b] *= a0; O[4 * b + 1] *= a0; O[4 * b + 2] *= a1; O[4 * b + 3] *= a1; }
  }
  n0 = m0; n1 = m1;
  float a[2];
  exp_range<0, 16>(S, n0, n1, a);
  r0 = a[0]; r1 = a[1];
  cvt_p(P, S);
}

template <int B>
__device__ __forceinline__ void mask_half(float (&S)[64], int thr) {
#pragma unroll
  for (int b = 0; b < 8; b++) {
    const bool m0 = 8 * b > thr, m1 = 8 * b + 1 > thr;
    if (m0) S[B + 4 * b] = -INFINITY;
    if (m1) S[B + 4 * b + 1] = -INFINITY;
    if (b < 7) {
      if (m0) S[B + 4 * b + 6] = -INFINITY;
      if (m1) S[B + 4 * b + 7] = -INFINITY;
    }
  }
}
__device__ __forceinline__ void issue_km_half(float (&S)[64], const uint32_t* A, uint32_t slot) {
  const uint32_t lo = desc_lo(slot, 16);
#pragma unroll
  for (int kk = 0; kk < 8; kk++)
    wgmma_rs_n64<0>(S, A[4 * kk], A[4 * kk + 1], A[4 * kk + 2], A[4 * kk + 3], desc_from(lo + (kk >> 2) * 1024 + (kk & 3) * 2), kk > 0);
}
template <int KSTEPS>
__device__ __forceinline__ void issue_pv(float (&O)[64], const uint32_t (&P)[32], uint32_t slot, int accumulate) {
  const uint32_t lo = desc_lo(slot, HALF_B);
#pragma unroll
  for (int kk = 0; kk < KSTEPS; kk++)
    wgmma_rs_n128<1>(O, P[4 * kk], P[4 * kk + 1], P[4 * kk + 2], P[4 * kk + 3], desc_from(lo + kk * 128), (kk > 0) ? 1 : accumulate);
}
template <int I0, int I1>
__device__ __forceinline__ void cvt_range(uint32_t (&P)[32], const float (&S)[64]) {
#pragma unroll
  for (int i = I0; i < I1; i++) P[i] = pack_bf16(S[2 * i], S[2 * i + 1]);
}

__device__ __forceinline__ void attn_consumer(const int WG, uint32_t sb, Ring r) {
  const uint32_t full0 = sb + RING_BAR, empty0 = full0 + 8 * NS;
  const int tid = threadIdx.x & 127, warp = __shfl_sync(0xffffffff, tid >> 5, 0), lane = tid & 31;
  const bool el = lane == 0;
  const uint32_t stg = sb + RING_STG + WG * 16384 + warp * 4096;
  const int row0 = WG * 64 + warp * 16;
  const uint32_t anchor_a = sb + RING_BAR + 128;
  auto thr_half = [&]() { const int l = fresh_lane(); return warp * 16 + (l >> 2) - 2 * (l & 3); };
  float O[64], S[64];
  uint32_t P[32], Q[32];
  float n0 = 0.f, n1 = 0.f, l0 = 0.f, l1 = 0.f;
  auto load_q_at = [&](const Ring& q) {
    mbar_wait(full0 + 8 * q.s, q.ph);
    load_frags(Q, sb + q.s * TILE_B, row0, fresh_lane());
    __syncwarp();
    mbar_arrive_if(empty0 + 8 * q.s, el);
  };
  auto read_item = [&](int i) {
    int v;
    asm volatile("ld.shared.s32 %0, [%1];" : "=r"(v) : "r"(sb + RING_ITEMS + (i & 3) * 4) : "memory");
    return __shfl_sync(0xffffffff, v, 0);
  };
  mbar_wait(full0 + 8 * r.s, r.ph);
  int it = 0, item = read_item(0), nb = (item & 15) + 1, prev_item = 0;
  if (item < 0) return;
  load_q_at(r); r.next();
  {
    const uint32_t ks = r.s;
    mbar_wait(full0 + 8 * r.s, r.ph);
    r.next();
    bar_sync(1 + WG, 256);
    fence_regs(S); fence_regs(Q);
    wg_fence();
    issue_km(S, Q, sb + ks * TILE_B);
    wg_commit();
    bar_arrive(1 + (WG ^ 1), 256);
    wg_wait<0>();
    fence_regs(S); fence_regs(Q);
    mbar_arrive_if(empty0 + 8 * ks, el);
    if (nb == 1) apply_mask(S, thr_half() + WG * 64);
    true_max_shift(S, n0, n1);
    float a[2];
    exp_range<0, 16>(S, n0, n1, a);
    l0 = a[0]; l1 = a[1];
    cvt_range<0, 32>(P, S);
  }
  int j = 1;
  bool more = true;
  if (nb == 1) {
    const int nxt = read_item(1);
    if (nxt < 0) more = false;
    else { load_q_at(r); r.next(); it = 1; j = 0; prev_item = item; item = nxt; nb = (item & 15) + 1; }
  }
  uint32_t ks = r.s, kph = r.ph; r.next();
  uint32_t vs = r.s, vph = r.ph; r.next();
  bool ready = false;
  int prev_acc = 0, pend = -1;
  while (more) {
    const bool first = j == 0, diag = j == nb - 1;
    const uint32_t kcur = ks, vcur = vs;
    const int acc_now = prev_acc;
    const Ring qr = r;
    float a[2];
    auto head_sync = [&]() {
      if (!ready) { mbar_wait(full0 + 8 * ks, kph); mbar_wait(full0 + 8 * vs, vph); }
      bar_sync(1 + WG, 256);
      fence_regs(S); fence_regs(Q); fence_regs(O); fence_regs(P);
      wg_fence();
    };
    auto window = [&](bool is_first, bool is_diag) {
      if (pend >= 0) { store_tile_rows(g_q + (size_t)pend * TILE_B, row0, stg, el); pend = -1; }
      prev_acc = !is_first;
      if (is_diag) {
        const int nxt = read_item(it + 1);
        more = nxt >= 0;
        if (more) { r.next(); ++it; j = 0; prev_item = item; item = nxt; nb = (item & 15) + 1; }
      } else ++j;
      ks = r.s; kph = r.ph;
      ready = false;
      if (more) {
        r.next(); vs = r.s; vph = r.ph; r.next();
        const bool t0 = mbar_test(full0 + 8 * ks, kph), t1 = mbar_test(full0 + 8 * vs, vph);
        ready = t0 && t1;
      }
    };
    auto pv_done = [&]() {
      wg_wait<0>();
      fence_regs(O); fence_regs(P);
      mbar_arrive_if(empty0 + 8 * vcur, el);
    };
    if (first) {
      const int done_item = prev_item;
      head_sync();
      issue_km(S, Q, sb + kcur * TILE_B);
      wg_commit();
      window(true, diag);
      if (el) bulk_wait_read<0>();
      __syncwarp();
      if (WG == 0) { issue_pv<4>(O, P, sb + vcur * TILE_B, acc_now); wg_commit(); }
      else { issue_pv<8>(O, P, sb + vcur * TILE_B, acc_now); wg_commit(); }
      bar_arrive(1 + (WG ^ 1), 256);
      wg_wait<1>();
      fence_regs(S); fence_regs(Q);
      if (diag) apply_mask(S, thr_half() + WG * 64);
      n0 = -SM_C * quad_max(fmaxf(fmaxf(S[0], S[1]), fmaxf(S[4], S[5])));
      n1 = -SM_C * quad_max(fmaxf(fmaxf(S[2], S[3]), fmaxf(S[6], S[7])));
      exp_range<0, 8>(S, n0, n1, a);
      anchor_sts(anchor_a, a[0] + a[1]);
      pv_done();
      exp_range<8, 16>(S, n0, n1, a);
      cvt_range<0, 32>(P, S);
      stage_tile(O, rcp_fast(quad_sum(l0)), rcp_fast(quad_sum(l1)), stg, fresh_lane());
      pend = done_item;
    } else if (diag && WG == 0) {
      head_sync();
      issue_km_half(S, Q, sb + kcur * TILE_B);
      wg_commit();
      window(false, true);
      issue_pv<8>(O, P, sb + vcur * TILE_B, acc_now);
      wg_commit();
      bar_arrive(1 + (WG ^ 1), 256);
      wg_wait<1>();
      fence_regs(S); fence_regs(Q);
      mask_half<0>(S, thr_half());
      exp_range<0, 8>(S, n0, n1, a);
      anchor_sts(anchor_a, a[0] + a[1]);
      pv_done();
      cvt_range<0, 16>(P, S);
    } else if (diag) {
      head_sync();
      issue_km(S, Q, sb + kcur * TILE_B);
      wg_commit();
      window(false, true);
      issue_pv<8>(O, P, sb + vcur * TILE_B, acc_now);
      wg_commit();
      bar_arrive(1 + (WG ^ 1), 256);
      wg_wait<1>();
      fence_regs(S); fence_regs(Q);
      mask_half<32>(S, thr_half());
      exp_range<0, 10>(S, n0, n1, a);
      anchor_sts(anchor_a, a[0] + a[1]);
      pv_done();
      exp_range<10, 16>(S, n0, n1, a);
      cvt_range<0, 32>(P, S);
    } else {
      head_sync();
      issue_km(S, Q, sb + kcur * TILE_B);
      wg_commit();
      window(false, false);
      issue_pv<8>(O, P, sb + vcur * TILE_B, acc_now);
      wg_commit();
      bar_arrive(1 + (WG ^ 1), 256);
      wg_wait<1>();
      fence_regs(S); fence_regs(Q);
      exp_range<0, 10>(S, n0, n1, a);
      anchor_sts(anchor_a, a[0] + a[1]);
      pv_done();
      exp_range<10, 16>(S, n0, n1, a);
      cvt_range<0, 32>(P, S);
    }
    float r0 = a[0], r1 = a[1];
    if (__any_sync(0xffffffff, !(fmaxf(r0, r1) < SM_LIMIT)))
      slow_block(S, O, P, Q, sb + kcur * TILE_B, fresh_lane(), diag, thr_half() + WG * 64, first, n0, n1, l0, l1, r0, r1);
    mbar_arrive_if(empty0 + 8 * kcur, el);
    l0 = first ? r0 : l0 + r0; l1 = first ? r1 : l1 + r1;
    if (diag && more) load_q_at(qr);
  }
  vs = ks;
  mbar_wait(full0 + 8 * vs, kph);
  bar_sync(1 + WG, 256);
  fence_regs(O); fence_regs(P);
  wg_fence();
  if (WG == 0) { issue_pv<4>(O, P, sb + vs * TILE_B, prev_acc); wg_commit(); }
  else { issue_pv<8>(O, P, sb + vs * TILE_B, prev_acc); wg_commit(); }
  bar_arrive(1 + (WG ^ 1), 256);
  if (pend >= 0) store_tile_rows(g_q + (size_t)pend * TILE_B, row0, stg, el);
  l0 = rcp_fast(quad_sum(l0)); l1 = rcp_fast(quad_sum(l1));
  if (el) bulk_wait_read<0>();
  __syncwarp();
  wg_wait<0>();
  fence_regs(O);
  stage_tile(O, l0, l1, stg, fresh_lane());
  store_tile_rows(g_q + (size_t)item * TILE_B, row0, stg, el);
  if (el) bulk_wait_read<0>();
}

__device__ __forceinline__ int fetch_item() {
  const int i = atomicAdd(&g_next, 1);
  if (i < 208) { const int g = i >= 104, r = i - g * 104; return (16 + g * 8 + (r & 7)) * 16 + 15 - (r >> 3); }
  if (i < 416) { const int r = i - 208; return ((r & 15) ^ 8) * 16 + 15 - (r >> 4); }
  if (i < NH * NRB) { const int r = i - 416; return (31 - (r & 31)) * 16 + 2 - (r >> 5); }
  return -1;
}

__device__ __forceinline__ void attn_producer(uint32_t sb, Ring& r) {
  const uint32_t full0 = sb + RING_BAR, empty0 = full0 + 8 * NS;
  auto load_tile = [&](const uint8_t* src) {
    mbar_wait(empty0 + 8 * r.s, r.ph);
    mbar_expect_tx(full0 + 8 * r.s, TILE_B);
    bulk_load(sb + r.s * TILE_B, src, TILE_B, full0 + 8 * r.s);
    r.next();
  };
  auto publish = [&](int i, int item) { asm volatile("st.shared.s32 [%0], %1;" :: "r"(sb + RING_ITEMS + (i & 3) * 4), "r"(item) : "memory"); };
  uint32_t seen = 0;
  auto need_head = [&](int h) { if (!((seen >> h) & 1)) { wait_count(&g_head[h], HEAD_DONE); seen |= 1u << h; } };
  const uint8_t* vprev = nullptr;
  int item = fetch_item();
  publish(0, item);
  if (item < 0) { mbar_wait(empty0 + 8 * r.s, r.ph); mbar_expect_tx(full0 + 8 * r.s, 0); return; }
  need_head(item >> 4);
  load_tile(g_q + (size_t)item * TILE_B);
  for (int it = 0; item >= 0; it++) {
    int next = -1;
    const int h = item >> 4, nb = (item & 15) + 1;
    const uint8_t* kb = g_k + (size_t)h * NRB * TILE_B;
    const uint8_t* vb = g_v + (size_t)h * NRB * TILE_B;
    for (int j = 0; j < nb; j++) {
      if (j == nb - 1) { next = fetch_item(); publish(it + 1, next); }
      load_tile(kb + (size_t)j * TILE_B);
      if (vprev) load_tile(vprev);
      vprev = vb + (size_t)j * TILE_B;
    }
    if (next >= 0) {
      need_head(next >> 4);
      load_tile(g_q + (size_t)next * TILE_B);
    }
    item = next;
  }
  load_tile(vprev);
}

__global__ void __launch_bounds__(384, 1) front_kernel(const __grid_constant__ ProjMaps maps, const __grid_constant__ FrontSched sched) {
  extern __shared__ uint8_t smem_raw[];
  const uint32_t sb = (smem_u32(smem_raw) + 1023) & ~1023u;
  const uint32_t full0 = sb + RING_BAR, empty0 = full0 + 8 * NS;
  const int cid = blockIdx.x;
  const int prb = sched.prb[cid], pinfo = sched.pinfo[cid];
  if (threadIdx.x == 0) {
    for (int i = 0; i < NS; i++) { mbar_init(full0 + 8 * i, 1); mbar_init(empty0 + 8 * i, 8); }
    mbar_init(sb + RING_PUB, 8); mbar_init(sb + RING_PUB + 8, 8);
    mbar_init_fence();
    if (blockIdx.x == 0) { for (int i = 0; i < 4 * NRB; i++) g_cnt[i] = 0; g_epoch++; }
  }
  __syncthreads();
  pdl_launch();
  const int wg = __shfl_sync(0xffffffff, threadIdx.x >> 7, 0);
  if (wg == 2) {
    reg_dec<24>();
    if (threadIdx.x == 256) {
      Ring r{0, 1};
      proj_producer(maps, prb, pinfo, sb, r);
      attn_producer(sb, r);
      if (cid < 128) {
        constexpr uint32_t WF = DM * FF * 2 / 128;
        bulk_prefetch(sched.wo + (size_t)cid * 32768, 32768);
        bulk_prefetch(sched.wg + (size_t)cid * WF, WF);
        bulk_prefetch(sched.wu + (size_t)cid * WF, WF);
        bulk_prefetch(sched.wd + (size_t)cid * WF, WF);
      }
    } else if (threadIdx.x == 288) {
      proj_publisher(pinfo, sb);
    }
  } else {
    reg_inc<240>();
    Ring r{0, 0};
    if (wg == 1) bar_arrive(1, 256);
    proj_consumer(wg, prb, pinfo, sb, r);
    attn_consumer(wg, sb, r);
  }
}

struct TailMaps { CUtensorMap wo, wg, wu, wd, x, out; };
constexpr int O_NS = 4, O_STAGE = 49152;
constexpr int D_NS = 5, D_X = D_NS * TILE_B;
constexpr int T_STG = NS * TILE_B;
constexpr int T_H = T_STG + 16384;
constexpr int T_BAR = T_H + 16384;
constexpr int T_SCALE = T_BAR + 512;
constexpr int T_SMEM = T_BAR + 1024 + 1024;
constexpr int B_OFULL = 0, B_OEMPTY = 4, B_GFULL = 8, B_GEMPTY = 14, B_DFULL = 20, B_DEMPTY = 25, B_ODONE = 30, B_STGFREE = 31,
              B_H = 32, B_X = 33, B_XFREE = 35;

__device__ __forceinline__ uint4 ld_relaxed_v4(const void* p) {
  uint4 v;
  asm volatile("ld.relaxed.gpu.global.v4.u32 {%0, %1, %2, %3}, [%4];" : "=r"(v.x), "=r"(v.y), "=r"(v.z), "=r"(v.w) : "l"(p) : "memory");
  return v;
}
__device__ __forceinline__ void st_relaxed_v4(void* p, uint32_t x, uint32_t y, uint32_t z, uint32_t w) {
  asm volatile("st.relaxed.gpu.global.v4.u32 [%0], {%1, %2, %3, %4};" :: "l"(p), "r"(x), "r"(y), "r"(z), "r"(w) : "memory");
}

__global__ void __launch_bounds__(384, 1) tail_kernel(const __grid_constant__ TailMaps maps) {
  extern __shared__ uint8_t smem_raw[];
  const uint32_t sb = (smem_u32(smem_raw) + 1023) & ~1023u;
  const uint32_t bar0 = sb + T_BAR;
  const uint32_t rank = cluster_rank();
  const int c = blockIdx.x >> 1;
  const int nh = (c >> 2) & 1, ks = c & 3, rb = (c >> 3) * 2 + rank, src = nh * 4 + ks;
  const int drb = c >> 2, nq = c & 3;
  const int gj = nq * 2 + rank, g0 = gj < 6 ? 3 * gj : 18 + 2 * (gj - 6), gn = gj < 6 ? 3 : 2;
  if (threadIdx.x == 256) { prefetch_map(&maps.wo); prefetch_map(&maps.x); prefetch_map(&maps.wg); prefetch_map(&maps.wu); prefetch_map(&maps.wd); prefetch_map(&maps.out); }
  if (threadIdx.x == 0) {
    for (int i = 0; i < O_NS; i++) { mbar_init(bar0 + 8 * (B_OFULL + i), 1); mbar_init(bar0 + 8 * (B_OEMPTY + i), 16); }
    for (int i = 0; i < NS; i++) { mbar_init(bar0 + 8 * (B_GFULL + i), 1); mbar_init(bar0 + 8 * (B_GEMPTY + i), 8); }
    for (int i = 0; i < D_NS; i++) { mbar_init(bar0 + 8 * (B_DFULL + i), 1); mbar_init(bar0 + 8 * (B_DEMPTY + i), 8); }
    mbar_init(bar0 + 8 * B_ODONE, 16); mbar_init(bar0 + 8 * B_STGFREE, 8);
    mbar_init(bar0 + 8 * B_H, 1); mbar_init(bar0 + 8 * B_X, 1); mbar_init(bar0 + 8 * (B_X + 1), 1); mbar_init(bar0 + 8 * B_XFREE, 8);
    mbar_expect_tx(bar0 + 8 * B_X, 16384);
    mbar_expect_tx(bar0 + 8 * (B_X + 1), 16384);
    mbar_init_fence();
  }
  __syncthreads();
  asm volatile("barrier.cluster.arrive.release.aligned;" ::: "memory");
  const int wg = __shfl_sync(0xffffffff, threadIdx.x >> 7, 0);
  if (wg == 2) {
    reg_dec<40>();
    asm volatile("barrier.cluster.wait.acquire.aligned;" ::: "memory");
    if (threadIdx.x == 256) {
      auto o_load_b = [&](int i) {
        const uint32_t st = sb + (i % O_NS) * O_STAGE, bar = bar0 + 8 * (B_OFULL + i % O_NS);
        mbar_expect_tx(bar, O_STAGE);
        const int k0 = ks * 1024 + i * 64;
        tma_load_2d_mc(st + HALF_B + (2 * rank) * 8192, &maps.wo, bar, nh * 256 + (2 * rank) * 64, k0, (uint16_t)3);
        tma_load_2d_mc(st + HALF_B + (2 * rank + 1) * 8192, &maps.wo, bar, nh * 256 + (2 * rank + 1) * 64, k0, (uint16_t)3);
      };
      auto o_load_a = [&](int i) {
        const int kh = ks * 16 + i;
        bulk_load(sb + (i % O_NS) * O_STAGE, g_q + (size_t)((kh >> 1) * NRB + rb) * TILE_B + (kh & 1) * HALF_B, HALF_B, bar0 + 8 * (B_OFULL + i % O_NS));
      };
      for (int i = 0; i < O_NS; i++) o_load_b(i);
      mbar_expect_tx(bar0 + 8 * B_H, HALF_B);
      tma_load_2d(sb + T_H, &maps.x, bar0 + 8 * B_H, nh * 256 + ks * 64, rb * 128);
      pdl_wait();
      if (blockIdx.x == 0) { for (int i = 0; i < NH; i++) g_head[i] = 0; g_next = 0; }
      for (int i = 0; i < O_NS; i++) o_load_a(i);
      for (int i = O_NS; i < 16; i++) {
        mbar_wait(bar0 + 8 * (B_OEMPTY + i % O_NS), ((i / O_NS) & 1) ^ 1);
        o_load_b(i);
        o_load_a(i);
      }
      auto g_load_w = [&](int u) {
        const uint32_t s = (u + 4) % NS, bar = bar0 + 8 * (B_GFULL + s);
        mbar_expect_tx(bar, TILE_B);
        tma_load_2d(sb + s * TILE_B, &maps.wg, bar, (g0 + (u >> 2)) * 64, (u & 3) * 128);
        tma_load_2d(sb + s * TILE_B + HALF_B, &maps.wu, bar, (g0 + (u >> 2)) * 64, (u & 3) * 128);
      };
      mbar_wait(bar0 + 8 * B_ODONE, 0);
      g_load_w(0);
      g_load_w(1);
      for (int kc = 0; kc < 4; kc++) mbar_expect_tx(bar0 + 8 * (B_GFULL + kc), kc == 0 ? TILE_B + 8192 : TILE_B);
      mbar_wait(bar0 + 8 * B_STGFREE, 0);
      wait_count(&g_cnt[drb], 64);
      bulk_load(sb + T_H, g_stat + drb * 8 * 128, 8192, bar0 + 8 * B_GFULL);
      for (int kc = 0; kc < 4; kc++)
        bulk_load_mc(sb + kc * TILE_B + rank * HALF_B, g_h + (size_t)(drb * 8 + 2 * kc + rank) * HALF_B, HALF_B, bar0 + 8 * (B_GFULL + kc), (uint16_t)3);
      for (int u = 2; u < 4 * gn; u++) {
        mbar_wait(bar0 + 8 * (B_GEMPTY + (u + 4) % NS), ((u + 4) / NS - 1) & 1);
        g_load_w(u);
      }
      const uint64_t order = rank ? 0x45cbace0da49ecull : 0x20a251c8149860ull;
      auto d_tile = [&](int i) { return (int)((order >> (5 * i)) & 31); };
      auto d_load_b = [&](int i) {
        const uint32_t st = sb + (i % D_NS) * TILE_B, bar = bar0 + 8 * (B_DFULL + i % D_NS);
        mbar_expect_tx(bar, TILE_B);
        tma_load_2d(st + HALF_B, &maps.wd, bar, nq * 128, d_tile(i) * 64);
        tma_load_2d(st + HALF_B + 8192, &maps.wd, bar, nq * 128 + 64, d_tile(i) * 64);
      };
      auto d_load_a = [&](int i) {
        bulk_load(sb + (i % D_NS) * TILE_B, g_act + (size_t)(drb * NFT + d_tile(i)) * HALF_B, HALF_B, bar0 + 8 * (B_DFULL + i % D_NS));
      };
      mbar_expect_tx(bar0 + 8 * B_H, 16384);
      bulk_load(sb + T_H, g_h + (size_t)(drb * 8 + 2 * nq + rank) * HALF_B, HALF_B, bar0 + 8 * B_H);
      wait_count(&g_cnt[NRB + drb * 3], 64);
      for (int k = 0; k < D_NS; k++) {
        const int i = gn == 3 ? (k + 4) % D_NS : k;
        const int uses = (4 + 4 * gn - i + NS - 1) / NS;
        mbar_wait(bar0 + 8 * (B_GEMPTY + i), (uses - 1) & 1);
        d_load_b(i);
        if (i < 4) d_load_a(i);
      }
      wait_count(&g_cnt[NRB + drb * 3 + 1], 64);
      d_load_a(4);
      for (int i = D_NS; i < 11; i++) {
        mbar_wait(bar0 + 8 * (B_DEMPTY + i % D_NS), ((i / D_NS) & 1) ^ 1);
        d_load_b(i);
        if (i == 8) wait_count(&g_cnt[NRB + drb * 3 + 2], 48);
        d_load_a(i);
      }
    }
  } else {
    reg_inc<232>();
    const int tid = threadIdx.x & 127, warp = __shfl_sync(0xffffffff, tid >> 5, 0), lane = tid & 31;
    const bool el = lane == 0, el1 = lane == 1;
    const int g = wg * 4 + warp;
    {
      float acc[128];
#pragma unroll
      for (int i = 0; i < 128; i++) acc[i] = 0.f;
      fence_regs(acc);
      for (int i = 0; i < 16; i++) {
        const uint32_t st = sb + (i % O_NS) * O_STAGE;
        mbar_wait(bar0 + 8 * (B_OFULL + i % O_NS), (i / O_NS) & 1);
        const uint32_t alo = desc_lo(st + wg * 8192, 16), blo = desc_lo(st + HALF_B, 8192);
        wg_fence();
#pragma unroll
        for (int kk = 0; kk < 4; kk++) wgmma_ss_n256<0, 1>(acc, desc_from(alo + kk * 2), desc_from(blo + kk * 128), 1);
        wg_commit();
        if (i > 0) {
          wg_wait<1>();
          mbar_arrive_if(bar0 + 8 * (B_OEMPTY + (i - 1) % O_NS), el);
          mbar_arrive_remote_if(bar0 + 8 * (B_OEMPTY + (i - 1) % O_NS), rank ^ 1, el1);
        }
      }
      wg_wait<0>();
      fence_regs(acc);
      mbar_arrive_if(bar0 + 8 * B_ODONE, el);
      mbar_arrive_remote_if(bar0 + 8 * B_ODONE, rank ^ 1, el1);
      const uint32_t tag = __ldcg(&g_epoch) & 1;
      uint8_t* pbase = g_part + (size_t)((rb * 2 + nh) * 16) * 16384 + g * 2048 + lane * 16;
      float own[32];
#pragma unroll
      for (int o = 0; o < 4; o++) {
        if (o != ks) {
#pragma unroll
          for (int ii = 0; ii < 4; ii++) {
            const int i = 4 * o + ii;
            st_relaxed_v4(pbase + (o * 4 + ks) * 16384 + ii * 512, (pack_bf16(acc[8 * i], acc[8 * i + 1]) & ~1u) | tag,
                          pack_bf16(acc[8 * i + 2], acc[8 * i + 3]), pack_bf16(acc[8 * i + 4], acc[8 * i + 5]), pack_bf16(acc[8 * i + 6], acc[8 * i + 7]));
          }
        } else {
#pragma unroll
          for (int e = 0; e < 32; e++) own[e] = acc[32 * o + e];
        }
      }
      uint32_t n = 0;
      while (true) {
        uint32_t bad = 0;
#pragma unroll
        for (int q = 0; q < 3; q++) bad |= ld_relaxed_v4(pbase + (ks * 4 + q + (q >= ks)) * 16384 + 3 * 512).x ^ tag;
        if (__all_sync(0xffffffff, !(bad & 1)) || ++n > (1u << 22)) break;
      }
      uint4 pu[3][4];
      bool ok;
      do {
        uint32_t bad = 0;
#pragma unroll
        for (int q = 0; q < 3; q++)
#pragma unroll
          for (int ii = 0; ii < 4; ii++) pu[q][ii] = ld_relaxed_v4(pbase + (ks * 4 + q + (q >= ks)) * 16384 + ii * 512);
#pragma unroll
        for (int q = 0; q < 3; q++)
#pragma unroll
          for (int ii = 0; ii < 4; ii++) bad |= pu[q][ii].x ^ tag;
        ok = __all_sync(0xffffffff, !(bad & 1));
      } while (!ok && ++n < (1u << 22));
#pragma unroll
      for (int q = 0; q < 3; q++)
#pragma unroll
        for (int ii = 0; ii < 4; ii++) pu[q][ii].x &= ~1u;
      mbar_wait(bar0 + 8 * B_H, 0);
      const uint32_t row = g * 16 + (lane & 7) + ((lane >> 3) & 1) * 8;
      const uint32_t xb = sb + T_H + row * 128;
      float hv[2][16];
#pragma unroll
      for (int ii = 0; ii < 4; ii++) {
        const uint32_t a = xb + (((ii * 2 + (lane >> 4)) ^ (row & 7)) << 4);
        uint32_t xw[4], hw[4];
        ldsm_x4(a, xw[0], xw[1], xw[2], xw[3]);
#pragma unroll
        for (int e = 0; e < 4; e++) {
          float lo = own[8 * ii + 2 * e], hi = own[8 * ii + 2 * e + 1];
#pragma unroll
          for (int q = 0; q < 3; q++) {
            const uint32_t w = e == 0 ? pu[q][ii].x : e == 1 ? pu[q][ii].y : e == 2 ? pu[q][ii].z : pu[q][ii].w;
            lo += bf_lo(w); hi += bf_hi(w);
          }
          const uint32_t at = pack_bf16(lo, hi);
          hw[e] = pack_bf16(bf_lo(xw[e]) + bf_lo(at), bf_hi(xw[e]) + bf_hi(at));
          hv[e & 1][4 * ii + (e >> 1) * 2] = bf_lo(hw[e]); hv[e & 1][4 * ii + (e >> 1) * 2 + 1] = bf_hi(hw[e]);
        }
        stsm_x4(a, hw[0], hw[1], hw[2], hw[3]);
      }
#pragma unroll
      for (int rr = 0; rr < 2; rr++) {
        float sum = 0.f, m2 = 0.f;
#pragma unroll
        for (int e = 0; e < 16; e++) sum += hv[rr][e];
        sum = quad_sum(sum);
        const float m = sum * (1.f / 64);
#pragma unroll
        for (int e = 0; e < 16; e++) m2 = fmaf(hv[rr][e] - m, hv[rr][e] - m, m2);
        m2 = quad_sum(m2);
        if ((lane & 3) == 0) asm volatile("st.shared.v2.f32 [%0], {%1, %2};" :: "r"(sb + T_STG + g * 2048 + (rr * 8 + (lane >> 2)) * 8), "f"(sum), "f"(m2) : "memory");
      }
      fence_async_smem();
      __syncwarp();
      if (el) {
        bulk_store(g_stat + (rb * 8 + src) * 128 + g * 16, sb + T_STG + g * 2048, 128);
        bulk_store(g_h + (size_t)(rb * 8 + src) * HALF_B + g * 2048, sb + T_H + g * 2048, 2048);
        bulk_commit();
        bulk_wait_read<0>();
        mbar_arrive_if(bar0 + 8 * B_STGFREE, true);
        bulk_wait<0>();
        signal_after_bulk(&g_cnt[rb]);
      }
      __syncwarp();
    }
    {
      const uint32_t stg = sb + T_STG + g * 2048;
      const int row0 = wg * 64 + warp * 16;
      uint32_t A[128];
      float acc[64];
      const uint32_t scale_a = sb + T_SCALE + (row0 + (lane >> 2)) * 4;
      uint32_t m0, m1;
      {
        mbar_wait(bar0 + 8 * B_GFULL, 0);
        uint32_t mm[2];
#pragma unroll
        for (int rr = 0; rr < 2; rr++) {
          float2 st[8];
          float sum = 0.f, m2 = 0.f;
#pragma unroll
          for (int q = 0; q < 8; q++) {
            asm volatile("ld.shared.v2.f32 {%0, %1}, [%2];" : "=f"(st[q].x), "=f"(st[q].y) : "r"(sb + T_H + (q * 128 + row0 + rr * 8 + (lane >> 2)) * 8) : "memory");
            sum += st[q].x;
          }
          const float mean = sum * (1.f / DM);
#pragma unroll
          for (int q = 0; q < 8; q++) { const float d = st[q].x * (1.f / 64) - mean; m2 += fmaf(64.f * d, d, st[q].y); }
          mm[rr] = pack_bf16(mean, mean);
          const float inv = rcp_fast(bf_round(sqrtf(bf_round(bf_round(m2 * (1.f / DM)) + 1e-5f))));
          if ((lane & 3) == 0) asm volatile("st.shared.f32 [%0], %1;" :: "r"(scale_a + rr * 32), "f"(inv) : "memory");
        }
        m0 = mm[0]; m1 = mm[1];
        __syncwarp();
      }
#pragma unroll
      for (int kc = 0; kc < 4; kc++) {
        mbar_wait(bar0 + 8 * (B_GFULL + kc), 0);
        load_frags(&A[32 * kc], sb + kc * TILE_B, row0, lane);
        __syncwarp();
        mbar_arrive_if(bar0 + 8 * (B_GEMPTY + kc), el);
#pragma unroll
        for (int i = 0; i < 32; i++) A[32 * kc + i] = bf2_sub(A[32 * kc + i], (i & 1) ? m1 : m0);
      }
      if (wg == 1) bar_arrive(1, 256);
      uint32_t s = 4, pass = 0;
      for (int t = 0; t < gn; t++) {
        bar_sync(1 + wg, 256);
        fence_regs(A); fence_regs(acc);
        uint32_t prev = 0;
#pragma unroll
        for (int kc = 0; kc < 4; kc++) {
          mbar_wait(bar0 + 8 * (B_GFULL + s), pass & 1);
          if (kc == 0) wg_fence();
          issue_mn(acc, &A[32 * kc], sb + s * TILE_B, kc > 0);
          wg_commit();
          if (kc == 3) {
            bar_arrive(1 + (wg ^ 1), 256);
            if (t > 0 && el) { bulk_wait<0>(); signal_after_bulk(&g_cnt[NRB + drb * 3 + t - 1]); }
          }
          if (kc > 0) { wg_wait<1>(); mbar_arrive_if(bar0 + 8 * (B_GEMPTY + prev), el); }
          prev = s;
          if (++s == NS) { s = 0; pass++; }
        }
        wg_wait<0>();
        fence_regs(acc); fence_regs(A);
        mbar_arrive_if(bar0 + 8 * (B_GEMPTY + prev), el);
        __syncwarp();
        uint32_t w[16];
        float i0, i1;
        asm volatile("ld.shared.f32 %0, [%1];" : "=f"(i0) : "r"(scale_a) : "memory");
        asm volatile("ld.shared.f32 %0, [%1];" : "=f"(i1) : "r"(scale_a + 32) : "memory");
#pragma unroll
        for (int i = 0; i < 16; i++) {
          const float sc = (i & 1) ? i1 : i0;
          const uint32_t gp = pack_bf16(acc[2 * i] * sc, acc[2 * i + 1] * sc), up = pack_bf16(acc[32 + 2 * i] * sc, acc[32 + 2 * i + 1] * sc);
          w[i] = bf2_mul(bf2_relu(gp), up);
        }
        const uint32_t row = (lane & 7) + ((lane >> 3) & 1) * 8;
#pragma unroll
        for (int kk = 0; kk < 4; kk++) {
          const uint32_t c16 = kk * 2 + (lane >> 4);
          stsm_x4(stg + row * 128 + ((c16 ^ (row & 7)) << 4), w[4 * kk], w[4 * kk + 1], w[4 * kk + 2], w[4 * kk + 3]);
        }
        fence_async_smem();
        __syncwarp();
        if (el) { bulk_store(g_act + (size_t)(drb * NFT + g0 + t) * HALF_B + row0 * 128, stg, 2048); bulk_commit(); }
      }
      mbar_arrive_remote_if(bar0 + 8 * B_XFREE, rank ^ 1, el);
      if (el) { bulk_wait<0>(); signal_after_bulk(&g_cnt[NRB + drb * 3 + gn - 1]); }
      __syncwarp();
    }
    {
      float acc[64];
#pragma unroll
      for (int i = 0; i < 64; i++) acc[i] = 0.f;
      fence_regs(acc);
      for (int i = 0; i < 11; i++) {
        const uint32_t st = sb + (i % D_NS) * TILE_B;
        mbar_wait(bar0 + 8 * (B_DFULL + i % D_NS), (i / D_NS) & 1);
        const uint32_t alo = desc_lo(st + wg * 8192, 16), blo = desc_lo(st + HALF_B, 8192);
        wg_fence();
#pragma unroll
        for (int kk = 0; kk < 4; kk++) wgmma_ss_n128<0, 1>(acc, desc_from(alo + kk * 2), desc_from(blo + kk * 128), 1);
        wg_commit();
        if (i > 0) { wg_wait<1>(); mbar_arrive_if(bar0 + 8 * (B_DEMPTY + (i - 1) % D_NS), el); }
      }
      wg_wait<0>();
      fence_regs(acc);
      {
        uint32_t ra, rbar;
        asm volatile("mapa.shared::cluster.u32 %0, %1, %2;" : "=r"(ra) : "r"(sb + D_X + wg * 16384 + tid * 16), "r"(rank ^ 1));
        asm volatile("mapa.shared::cluster.u32 %0, %1, %2;" : "=r"(rbar) : "r"(bar0 + 8 * (B_X + wg)), "r"(rank ^ 1));
        mbar_wait_cluster(bar0 + 8 * B_XFREE, 0);
#pragma unroll
        for (int i = 0; i < 8; i++) {
          const float a0 = rank ? acc[4 * i] : acc[32 + 4 * i], a1 = rank ? acc[4 * i + 1] : acc[32 + 4 * i + 1];
          const float a2 = rank ? acc[4 * i + 2] : acc[32 + 4 * i + 2], a3 = rank ? acc[4 * i + 3] : acc[32 + 4 * i + 3];
          asm volatile("st.async.weak.shared::cluster.mbarrier::complete_tx::bytes.v4.f32 [%0], {%1, %2, %3, %4}, [%5];"
                       :: "r"(ra + i * 2048), "f"(a0), "f"(a1), "f"(a2), "f"(a3), "r"(rbar) : "memory");
        }
      }
      mbar_wait(bar0 + 8 * B_H, 1);
      mbar_wait_cluster(bar0 + 8 * (B_X + wg), 0);
      const uint32_t row = g * 16 + (lane & 7) + ((lane >> 3) & 1) * 8;
      const uint32_t hb = sb + T_H + row * 128;
#pragma unroll
      for (int kk = 0; kk < 4; kk++) {
        float p[8];
        asm volatile("ld.shared.v4.f32 {%0, %1, %2, %3}, [%4];" : "=f"(p[0]), "=f"(p[1]), "=f"(p[2]), "=f"(p[3]) : "r"(sb + D_X + wg * 16384 + tid * 16 + (2 * kk) * 2048) : "memory");
        asm volatile("ld.shared.v4.f32 {%0, %1, %2, %3}, [%4];" : "=f"(p[4]), "=f"(p[5]), "=f"(p[6]), "=f"(p[7]) : "r"(sb + D_X + wg * 16384 + tid * 16 + (2 * kk + 1) * 2048) : "memory");
        const uint32_t a = hb + (((kk * 2 + (lane >> 4)) ^ (row & 7)) << 4);
        uint32_t hw[4], ow[4];
        ldsm_x4(a, hw[0], hw[1], hw[2], hw[3]);
#pragma unroll
        for (int e = 0; e < 4; e++) {
          const float lo = (rank ? acc[32 + 8 * kk + 2 * e] : acc[8 * kk + 2 * e]) + p[2 * e];
          const float hi = (rank ? acc[32 + 8 * kk + 2 * e + 1] : acc[8 * kk + 2 * e + 1]) + p[2 * e + 1];
          const uint32_t d = pack_bf16(lo, hi);
          ow[e] = pack_bf16(bf_lo(hw[e]) + bf_lo(d), bf_hi(hw[e]) + bf_hi(d));
        }
        stsm_x4(a, ow[0], ow[1], ow[2], ow[3]);
      }
      fence_async_smem();
      __syncwarp();
      if (el) {
        tma_store_2d(&maps.out, sb + T_H + g * 2048, nq * 128 + rank * 64, drb * 128 + g * 16);
        bulk_commit();
        bulk_wait_read<0>();
      }
    }
  }
}

typedef CUresult (*EncodeTiledFn)(CUtensorMap*, CUtensorMapDataType, cuuint32_t, void*, const cuuint64_t*, const cuuint64_t*, const cuuint32_t*,
                                  const cuuint32_t*, CUtensorMapInterleave, CUtensorMapSwizzle, CUtensorMapL2promotion, CUtensorMapFloatOOBfill);

CUtensorMap make_map(EncodeTiledFn fn, const void* ptr, uint64_t cols, uint64_t rows, uint32_t box_cols, uint32_t box_rows) {
  CUtensorMap m;
  cuuint64_t dims[2] = {cols, rows};
  cuuint64_t strides[1] = {cols * 2};
  cuuint32_t box[2] = {box_cols, box_rows};
  cuuint32_t es[2] = {1, 1};
  fn(&m, CU_TENSOR_MAP_DATA_TYPE_BFLOAT16, 2, const_cast<void*>(ptr), dims, strides, box, es, CU_TENSOR_MAP_INTERLEAVE_NONE,
     CU_TENSOR_MAP_SWIZZLE_128B, CU_TENSOR_MAP_L2_PROMOTION_L2_128B, CU_TENSOR_MAP_FLOAT_OOB_FILL_NONE);
  return m;
}

void make_front_sched(FrontSched& s, int nworkers) {
  const int spare = nworkers - 128;
  int w = 0;
  for (int rb = 0; rb < NRB; rb++) {
    const int nc = rb < spare ? 6 : 5;
    for (int j = 0; j < 3 + nc; j++, w++) {
      const bool is_x = j < 3;
      s.prb[w] = (uint8_t)rb;
      s.pinfo[w] = (uint8_t)((is_x ? 128 : 0) | (is_x ? 3 : nc) << 3 | (is_x ? j : j - 3));
    }
  }
}

template <typename... KArgs, typename... Args>
void launch(void (*kern)(KArgs...), int grid, int smem, int cluster, bool pdl, cudaStream_t st, Args... args) {
  cudaLaunchConfig_t cfg = {};
  cfg.gridDim = dim3(grid); cfg.blockDim = dim3(384); cfg.dynamicSmemBytes = smem; cfg.stream = st;
  cudaLaunchAttribute at[2];
  int n = 0;
  if (cluster > 1) { at[n].id = cudaLaunchAttributeClusterDimension; at[n].val.clusterDim.x = cluster; at[n].val.clusterDim.y = 1; at[n].val.clusterDim.z = 1; n++; }
  if (pdl) { at[n].id = cudaLaunchAttributeProgrammaticStreamSerialization; at[n].val.programmaticStreamSerializationAllowed = 1; n++; }
  cfg.attrs = at; cfg.numAttrs = n;
  cudaLaunchKernelEx(&cfg, kern, KArgs(args)...);
}

}

extern "C" void kernel_launch(void* const* d_in, const int* in_sizes, int n_in, void* d_out, int out_size) {
  (void)in_sizes; (void)n_in; (void)out_size;
  static EncodeTiledFn encode = nullptr;
  static FrontSched sched;
  static int n_sm = 0;
  if (!encode) {
    void* p = nullptr;
    cudaDriverEntryPointQueryResult q;
    cudaGetDriverEntryPoint("cuTensorMapEncodeTiled", &p, cudaEnableDefault, &q);
    encode = (EncodeTiledFn)p;
    cudaDeviceGetAttribute(&n_sm, cudaDevAttrMultiProcessorCount, 0);
    if (n_sm > 132) n_sm = 132;
    make_front_sched(sched, n_sm);
    cudaFuncSetAttribute(front_kernel, cudaFuncAttributeMaxDynamicSharedMemorySize, RING_SMEM);
    cudaFuncSetAttribute(tail_kernel, cudaFuncAttributeMaxDynamicSharedMemorySize, T_SMEM);
  }
  const void *x = d_in[0], *ckv = d_in[1], *wq = d_in[2], *wuk = d_in[3], *wuv = d_in[4], *wo = d_in[5];
  const void *wg = d_in[7], *wu = d_in[8], *wd = d_in[9];
  ProjMaps pm;
  pm.x = make_map(encode, x, DM, SEQ, 64, 128);
  pm.c = make_map(encode, ckv, DM, SEQ, 64, 128);
  pm.wq = make_map(encode, wq, NH * HD, DM, 64, 128);
  pm.wuk = make_map(encode, wuk, NH * HD, DM, 64, 128);
  pm.wuv = make_map(encode, wuv, NH * HD, DM, 64, 128);
  TailMaps tm;
  tm.wo = make_map(encode, wo, DM, NH * HD, 64, 64);
  tm.wg = make_map(encode, wg, FF, DM, 64, 128);
  tm.wu = make_map(encode, wu, FF, DM, 64, 128);
  tm.wd = make_map(encode, wd, DM, FF, 64, 64);
  tm.x = pm.x;
  tm.out = make_map(encode, d_out, DM, SEQ, 64, 16);

  sched.wo = (const uint8_t*)wo; sched.wg = (const uint8_t*)wg; sched.wu = (const uint8_t*)wu; sched.wd = (const uint8_t*)wd;
  cudaStream_t st = cudaStreamPerThread;
  launch(front_kernel, n_sm, RING_SMEM, 1, false, st, pm, sched);
  launch(tail_kernel, 128, T_SMEM, 2, true, st, tm);
}
```
